```python
import torch

def _softmax(x, axis=-1):
    return torch.softmax(x, dim=axis)
def _gelu(x):
    return torch.nn.functional.gelu(x, approximate="tanh")
def _silu(x):
    return torch.nn.functional.silu(x)
def _sigmoid(x):
    return torch.sigmoid(x)
def _layernorm(x, axis=-1, eps=1e-5):
    m = x.mean(dim=axis, keepdim=True)
    v = x.var(dim=axis, keepdim=True, unbiased=False)
    return (x - m) / torch.sqrt(v + eps)
def _scatter_add(tgt, idx, src, axis=0):
    return tgt.clone().index_add_(axis, idx, src)
def _segment_sum(src, seg, n):
    out = torch.zeros((n,) + src.shape[1:], dtype=src.dtype)
    return out.index_add_(0, seg, src)
def _pad(x, pw):
    flat = tuple(v for pair in reversed(pw) for v in pair)
    return torch.nn.functional.pad(x, flat)

kernel_name = 'gated_mix__grouped_kv_mqa__moe_arch_mod__prompt'

def setup_inputs():

    _w = (lambda a: (lambda t: t.to(torch.bfloat16) if t.is_floating_point() else t)(torch.as_tensor(a)))
    def _A_setup():
        B, S, D, H = 1, 2048, 576, 32
        Dh = D // H
        return {
            "x": _w((lambda *s: torch.randn(*s, dtype=torch.bfloat16) * 0.05)(B, S, D)),
            "wq": _w((lambda *s: torch.randn(*s, dtype=torch.bfloat16) * 0.8)(D, H * Dh)),
            "wk": _w((lambda *s: torch.randn(*s, dtype=torch.bfloat16) * 0.8)(D, Dh)),
            "wv": _w((lambda *s: torch.randn(*s, dtype=torch.bfloat16) * 0.2)(D, Dh)),
            "wo": _w((lambda *s: torch.randn(*s, dtype=torch.bfloat16) * 0.2)(H * Dh, D)),
        }
    _A_in = _A_setup()

    def _B_setup():
        B, S, D, F, C = 1, 2048, 576, 4608, 1
        return {
            "x": _w((lambda *s: torch.randn(*s, dtype=torch.bfloat16) * 0.05)(B, S, D)),
            "w_r": _w((lambda *s: torch.randn(*s, dtype=torch.bfloat16) * 3.2)(D)),
            "w_gate": _w((lambda *s: torch.randn(*s, dtype=torch.bfloat16) * 0.2)(D, F)),
            "w_up": _w((lambda *s: torch.randn(*s, dtype=torch.bfloat16) * 0.2)(D, F)),
            "w_down": _w((lambda *s: torch.randn(*s, dtype=torch.bfloat16) * 0.2)(F, D)),
        }
    _B_in = _B_setup()

    return {
        "A_x": _A_in["x"],
        "A_wq": _A_in["wq"],
        "A_wk": _A_in["wk"],
        "A_wv": _A_in["wv"],
        "A_wo": _A_in["wo"],
        "B_x": _B_in["x"],
        "B_w_r": _B_in["w_r"],
        "B_w_gate": _B_in["w_gate"],
        "B_w_up": _B_in["w_up"],
        "B_w_down": _B_in["w_down"],
        "gate_w": _w((lambda *s: torch.randn(*s, dtype=torch.bfloat16) * 0.05)(576) * 16.0),
    }

def reference(A_x, A_wq, A_wk, A_wv, A_wo, B_x, B_w_r, B_w_gate, B_w_up, B_w_down, gate_w):
    def _A_ref(x, wq, wk, wv, wo):
        B, S, D = x.shape
        H = 32
        Dh = D // H
        q = (lambda x, *d: x.permute(*d))((x @ wq).reshape(B, S, H, Dh), 0, 2, 1, 3)
        k = x @ wk
        v = x @ wv
        scores = torch.einsum("bhqd,bkd->bhqk", q, k) * (Dh ** -0.5)
        p = _softmax(scores, axis=-1)
        o = torch.einsum("bhqk,bkd->bhqd", p, v)
        return (lambda x, *d: x.permute(*d))(o, 0, 2, 1, 3).reshape(B, S, H * Dh) @ wo

    def _B_ref(x, w_r, w_gate, w_up, w_down):
        B, S, D = x.shape
        C = 1
        r = x @ w_r
        idx = torch.argsort(-r, axis=-1)[:, :C]
        idx_e = (lambda x, n, axis: torch.repeat_interleave(x, n, dim=axis))(idx.reshape(B, C, 1), D, axis=2)
        x_sel = (lambda x, i, axis: torch.take_along_dim(x, i, dim=axis))(x, idx_e, axis=1)
        g = _silu(x_sel @ w_gate)
        u = x_sel @ w_up
        y = (g * u) @ w_down
        r_sel = _sigmoid((lambda x, i, axis: torch.take_along_dim(x, i, dim=axis))(r, idx, axis=1))
        y = y * r_sel.reshape(B, C, 1)
        b_off = (torch.arange(B) * S).reshape(B, 1)
        flat_idx = (idx + b_off).reshape(B * C)
        zero = (x * 0.0).reshape(B * S, D)
        upd = _scatter_add(zero, flat_idx, y.reshape(B * C, D), axis=0)
        return x + upd.reshape(B, S, D)

    x = A_x
    g = _sigmoid((x * gate_w).sum(-1, keepdims=True))
    a = _A_ref(x, A_wq, A_wk, A_wv, A_wo)
    b = _B_ref(x, B_w_r, B_w_gate, B_w_up, B_w_down)
    return g * a + (1 - g) * b
```

```cpp
#include <cuda_runtime.h>
#include <cuda_bf16.h>
#include <cuda_fp16.h>
#include <stdint.h>

constexpr int SEQ = 2048, DM = 576, FF = 4608, NSL = 144;
constexpr uint32_t PL = 32768;
constexpr uint32_t BPS = 576 * 16 + 16;
constexpr uint32_t KMASK = 0x25;

__device__ __nv_bfloat16 g_q[SEQ * DM];
__device__ __nv_bfloat16 g_o[SEQ * DM];
__device__ uint4 g_kv[5 * SEQ];
__device__ float g_kraw[SEQ * 18];
__device__ float g_vraw[SEQ * 18];
__device__ float g_gate[SEQ];
__device__ float4 g_stat[16];
__device__ float g_ypart[NSL * DM];

__device__ __forceinline__ void wgh_n64_sd0(uint32_t* d, uint32_t a0, uint32_t a1, uint32_t a2, uint32_t a3, uint64_t bdesc) {
  asm volatile("{\n.reg .pred p;\nsetp.ne.b32 p, 0, 0;\n"
    "wgmma.mma_async.sync.aligned.m64n64k16.f16.f16.f16 {%0, %1, %2, %3, %4, %5, %6, %7, %8, %9, %10, %11, %12, %13, %14, %15}, {%16, %17, %18, %19}, %20, p, 1, 1, 0;\n}\n"
    : "=r"(d[0]), "=r"(d[1]), "=r"(d[2]), "=r"(d[3]), "=r"(d[4]), "=r"(d[5]), "=r"(d[6]), "=r"(d[7]), "=r"(d[8]), "=r"(d[9]), "=r"(d[10]), "=r"(d[11]), "=r"(d[12]), "=r"(d[13]), "=r"(d[14]), "=r"(d[15]) : "r"(a0), "r"(a1), "r"(a2), "r"(a3), "l"(bdesc));
}
__device__ __forceinline__ void wgh_n64_sd1(uint32_t* d, uint32_t a0, uint32_t a1, uint32_t a2, uint32_t a3, uint64_t bdesc) {
  asm volatile("{\n.reg .pred p;\nsetp.ne.b32 p, 1, 0;\n"
    "wgmma.mma_async.sync.aligned.m64n64k16.f16.f16.f16 {%0, %1, %2, %3, %4, %5, %6, %7, %8, %9, %10, %11, %12, %13, %14, %15}, {%16, %17, %18, %19}, %20, p, 1, 1, 0;\n}\n"
    : "+r"(d[0]), "+r"(d[1]), "+r"(d[2]), "+r"(d[3]), "+r"(d[4]), "+r"(d[5]), "+r"(d[6]), "+r"(d[7]), "+r"(d[8]), "+r"(d[9]), "+r"(d[10]), "+r"(d[11]), "+r"(d[12]), "+r"(d[13]), "+r"(d[14]), "+r"(d[15]) : "r"(a0), "r"(a1), "r"(a2), "r"(a3), "l"(bdesc));
}
__device__ __forceinline__ void wg_pv(float* d, uint32_t a0, uint32_t a1, uint32_t a2, uint32_t a3, uint64_t bdesc) {
  asm volatile("{\n.reg .pred p;\nsetp.ne.b32 p, 1, 0;\n"
    "wgmma.mma_async.sync.aligned.m64n24k16.f32.f16.f16 {%0, %1, %2, %3, %4, %5, %6, %7, %8, %9, %10, %11}, {%12, %13, %14, %15}, %16, p, 1, 1, 1;\n}\n"
    : "+f"(d[0]), "+f"(d[1]), "+f"(d[2]), "+f"(d[3]), "+f"(d[4]), "+f"(d[5]), "+f"(d[6]), "+f"(d[7]), "+f"(d[8]), "+f"(d[9]), "+f"(d[10]), "+f"(d[11]) : "r"(a0), "r"(a1), "r"(a2), "r"(a3), "l"(bdesc));
}
__device__ __forceinline__ void wg_n80(float* d, uint32_t a0, uint32_t a1, uint32_t a2, uint32_t a3, uint64_t bdesc) {
  asm volatile("{\n.reg .pred p;\nsetp.ne.b32 p, 1, 0;\n"
    "wgmma.mma_async.sync.aligned.m64n80k16.f32.bf16.bf16 {%0, %1, %2, %3, %4, %5, %6, %7, %8, %9, %10, %11, %12, %13, %14, %15, %16, %17, %18, %19, %20, %21, %22, %23, %24, %25, %26, %27, %28, %29, %30, %31, %32, %33, %34, %35, %36, %37, %38, %39}, {%40, %41, %42, %43}, %44, p, 1, 1, 1;\n}\n"
    : "+f"(d[0]), "+f"(d[1]), "+f"(d[2]), "+f"(d[3]), "+f"(d[4]), "+f"(d[5]), "+f"(d[6]), "+f"(d[7]), "+f"(d[8]), "+f"(d[9]), "+f"(d[10]), "+f"(d[11]), "+f"(d[12]), "+f"(d[13]), "+f"(d[14]), "+f"(d[15]), "+f"(d[16]), "+f"(d[17]), "+f"(d[18]), "+f"(d[19]), "+f"(d[20]), "+f"(d[21]), "+f"(d[22]), "+f"(d[23]), "+f"(d[24]), "+f"(d[25]), "+f"(d[26]), "+f"(d[27]), "+f"(d[28]), "+f"(d[29]), "+f"(d[30]), "+f"(d[31]), "+f"(d[32]), "+f"(d[33]), "+f"(d[34]), "+f"(d[35]), "+f"(d[36]), "+f"(d[37]), "+f"(d[38]), "+f"(d[39]) : "r"(a0), "r"(a1), "r"(a2), "r"(a3), "l"(bdesc));
}
__device__ __forceinline__ void wg_n72(float* d, uint32_t a0, uint32_t a1, uint32_t a2, uint32_t a3, uint64_t bdesc) {
  asm volatile("{\n.reg .pred p;\nsetp.ne.b32 p, 1, 0;\n"
    "wgmma.mma_async.sync.aligned.m64n72k16.f32.bf16.bf16 {%0, %1, %2, %3, %4, %5, %6, %7, %8, %9, %10, %11, %12, %13, %14, %15, %16, %17, %18, %19, %20, %21, %22, %23, %24, %25, %26, %27, %28, %29, %30, %31, %32, %33, %34, %35}, {%36, %37, %38, %39}, %40, p, 1, 1, 1;\n}\n"
    : "+f"(d[0]), "+f"(d[1]), "+f"(d[2]), "+f"(d[3]), "+f"(d[4]), "+f"(d[5]), "+f"(d[6]), "+f"(d[7]), "+f"(d[8]), "+f"(d[9]), "+f"(d[10]), "+f"(d[11]), "+f"(d[12]), "+f"(d[13]), "+f"(d[14]), "+f"(d[15]), "+f"(d[16]), "+f"(d[17]), "+f"(d[18]), "+f"(d[19]), "+f"(d[20]), "+f"(d[21]), "+f"(d[22]), "+f"(d[23]), "+f"(d[24]), "+f"(d[25]), "+f"(d[26]), "+f"(d[27]), "+f"(d[28]), "+f"(d[29]), "+f"(d[30]), "+f"(d[31]), "+f"(d[32]), "+f"(d[33]), "+f"(d[34]), "+f"(d[35]) : "r"(a0), "r"(a1), "r"(a2), "r"(a3), "l"(bdesc));
}

__device__ __forceinline__ void wg_fence() { asm volatile("wgmma.fence.sync.aligned;" ::: "memory"); }
__device__ __forceinline__ void wg_commit() { asm volatile("wgmma.commit_group.sync.aligned;" ::: "memory"); }
template<int N> __device__ __forceinline__ void wg_wait() { asm volatile("wgmma.wait_group.sync.aligned %0;" :: "n"(N) : "memory"); }
__device__ __forceinline__ uint32_t pack2(float lo, float hi) { uint32_t r; asm("cvt.rn.bf16x2.f32 %0, %1, %2;" : "=r"(r) : "f"(hi), "f"(lo)); return r; }
__device__ __forceinline__ uint32_t pack2h(float lo, float hi) { uint32_t r; asm("cvt.rn.f16x2.f32 %0, %1, %2;" : "=r"(r) : "f"(hi), "f"(lo)); return r; }
__device__ __forceinline__ float bflo(uint32_t v) { return __uint_as_float(v << 16); }
__device__ __forceinline__ float bfhi(uint32_t v) { return __uint_as_float(v & 0xffff0000u); }
__device__ __forceinline__ float bfr(float v) { return __bfloat162float(__float2bfloat16(v)); }
__device__ __forceinline__ uint32_t hfma2(uint32_t a, uint32_t b, uint32_t c) { uint32_t r; asm("fma.rn.f16x2 %0, %1, %2, %3;" : "=r"(r) : "r"(a), "r"(b), "r"(c)); return r; }
__device__ __forceinline__ uint32_t hfma2r(uint32_t a, uint32_t b, uint32_t c) { uint32_t r; asm("fma.rn.relu.f16x2 %0, %1, %2, %3;" : "=r"(r) : "r"(a), "r"(b), "r"(c)); return r; }
__device__ __forceinline__ uint32_t ex2h2(uint32_t x) { uint32_t r; asm("ex2.approx.f16x2 %0, %1;" : "=r"(r) : "r"(x)); return r; }
__device__ __forceinline__ uint64_t mk64(uint32_t lo, uint32_t hi) { uint64_t d; asm("mov.b64 %0, {%1, %2};" : "=l"(d) : "r"(lo), "r"(hi)); return d; }
template<int N> __device__ __forceinline__ void fence_regs(float* r) {
  #pragma unroll
  for (int i = 0; i < N; i++) asm volatile("" : "+f"(r[i]) :: "memory");
}
template<int N> __device__ __forceinline__ void fence_regs(uint32_t* r) {
  #pragma unroll
  for (int i = 0; i < N; i++) asm volatile("" : "+r"(r[i]) :: "memory");
}
__device__ __forceinline__ void cp16(uint32_t dst, const void* src) { asm volatile("cp.async.cg.shared.global [%0], [%1], 16;" :: "r"(dst), "l"(src) : "memory"); }
__device__ __forceinline__ void cp4(uint32_t dst, const void* src) { asm volatile("cp.async.ca.shared.global [%0], [%1], 4;" :: "r"(dst), "l"(src) : "memory"); }
__device__ __forceinline__ void cp_commit() { asm volatile("cp.async.commit_group;" ::: "memory"); }
template<int N> __device__ __forceinline__ void cp_wait() { asm volatile("cp.async.wait_group %0;" :: "n"(N) : "memory"); }
__device__ __forceinline__ void proxy_fence() { asm volatile("fence.proxy.async.shared::cta;" ::: "memory"); }
__device__ __forceinline__ void pdl_wait() { asm volatile("griddepcontrol.wait;" ::: "memory"); }
__device__ __forceinline__ void pdl_go() { asm volatile("griddepcontrol.launch_dependents;" ::: "memory"); }
__device__ __forceinline__ uint4 ldg16(const void* p) { uint4 v; asm volatile("ld.global.nc.L1::no_allocate.v4.u32 {%0,%1,%2,%3}, [%4];" : "=r"(v.x), "=r"(v.y), "=r"(v.z), "=r"(v.w) : "l"(p)); return v; }
__device__ __forceinline__ uint4 ldg16c(const void* p) { uint4 v; asm volatile("ld.global.L1::no_allocate.v4.u32 {%0,%1,%2,%3}, [%4];" : "=r"(v.x), "=r"(v.y), "=r"(v.z), "=r"(v.w) : "l"(p) : "memory"); return v; }
__device__ __forceinline__ void mbar_wait(uint32_t bar, uint32_t parity) {
  #pragma unroll 1
  for (int it = 0; it < (1 << 22); it++) {
    uint32_t ok;
    asm volatile("{\n.reg .pred p;\nmbarrier.try_wait.parity.shared::cta.b64 p, [%1], %2;\nselp.u32 %0, 1, 0, p;\n}\n" : "=r"(ok) : "r"(bar), "r"(parity) : "memory");
    if (ok) break;
  }
}
__device__ __forceinline__ int kpos(int k) { return (k & ~31) | ((k & 4) << 2) | ((k & 2) << 2) | ((k >> 2) & 6) | (k & 1); }

template<int NB> __device__ __forceinline__ void loadB(uint32_t sb, const __nv_bfloat16* W, int k0, int tid) {
  #pragma unroll
  for (int i = 0; i < (192 * NB + 255) / 256; i++) {
    int id = tid + i * 256;
    if (id < 192 * NB) { int k = k0 + id / NB, nb = id % NB; cp16(sb + nb * BPS + kpos(k) * 16, W + (size_t)k * DM + nb * 8); }
  }
}

__global__ void __launch_bounds__(256, 1) k_proj(const __nv_bfloat16* __restrict__ x, const __nv_bfloat16* __restrict__ wq, const __nv_bfloat16* __restrict__ wk,
    const __nv_bfloat16* __restrict__ wv, const __nv_bfloat16* __restrict__ wr, const __nv_bfloat16* __restrict__ gw) {
  extern __shared__ __align__(1024) uint8_t smem[];
  pdl_go();
  const int tid = threadIdx.x, lane = tid & 31, g = lane >> 2, t = lane & 3, warp = tid >> 5;
  const int rt = blockIdx.x >> 3, ct = blockIdx.x & 7;
  const uint32_t sb = (uint32_t)__cvta_generic_to_shared(smem);
  const int r0 = rt * 128 + warp * 16 + g;
  const __nv_bfloat16* a0p = x + (size_t)r0 * DM + t * 8;
  uint4 va[18], vb[18];
  #pragma unroll
  for (int c = 0; c < 3; c++) {
    if (ct < 7) loadB<10>(sb, wq + ct * 80, c * 192, tid);
    else {
      loadB<2>(sb, wq + 560, c * 192, tid);
      #pragma unroll
      for (int i = 0; i < 14; i++) {
        int id = tid + i * 256;
        if (id < 192 * 18) {
          int k = c * 192 + id / 18, j = id % 18, col = 16 + 2 * j;
          const __nv_bfloat16* src = j < 9 ? wk + k * 18 + 2 * j : wv + k * 18 + 2 * (j - 9);
          cp4(sb + (col >> 3) * BPS + kpos(k) * 16 + (col & 7) * 2, src);
        }
      }
      if (tid < 192) {
        int k = c * 192 + tid;
        uint32_t w = (uint32_t)__bfloat16_as_ushort(wr[k]) | ((uint32_t)__bfloat16_as_ushort(gw[k]) << 16);
        *(uint2*)(smem + 6 * BPS + kpos(k) * 16 + 8) = make_uint2(w, 0u);
      }
    }
    cp_commit();
    #pragma unroll
    for (int b = c * 6; b < c * 6 + 6; b++) { va[b] = ldg16(a0p + b * 32); vb[b] = ldg16(a0p + 8 * DM + b * 32); }
  }
  float acc[40];
  #pragma unroll
  for (int i = 0; i < 40; i++) asm volatile("mov.b32 %0, 0;" : "=f"(acc[i]));
  const uint32_t dlo = (sb >> 4) | (8 << 16);
  #pragma unroll
  for (int c = 0; c < 3; c++) {
    if (c == 0) cp_wait<2>(); else if (c == 1) cp_wait<1>(); else cp_wait<0>();
    proxy_fence();
    __syncthreads();
    wg_fence();
    #pragma unroll
    for (int b = c * 6; b < c * 6 + 6; b++) {
      wg_n80(acc, va[b].x, vb[b].x, va[b].y, vb[b].y, mk64(dlo + b * 32, BPS >> 4));
      wg_n80(acc, va[b].z, vb[b].z, va[b].w, vb[b].w, mk64(dlo + b * 32 + 16, BPS >> 4));
    }
    wg_commit();
  }
  wg_wait<0>();
  fence_regs<40>(acc);
  uint32_t* q0 = (uint32_t*)(g_q + (size_t)r0 * DM + ct * 80) + t;
  if (ct < 7) {
    #pragma unroll
    for (int nb = 0; nb < 10; nb++) { q0[nb * 4] = pack2(acc[nb * 4], acc[nb * 4 + 1]); q0[4 * DM + nb * 4] = pack2(acc[nb * 4 + 2], acc[nb * 4 + 3]); }
  } else {
    #pragma unroll
    for (int nb = 0; nb < 2; nb++) { q0[nb * 4] = pack2(acc[nb * 4], acc[nb * 4 + 1]); q0[4 * DM + nb * 4] = pack2(acc[nb * 4 + 2], acc[nb * 4 + 3]); }
    __syncthreads();
    float* st = (float*)smem;
    const int lr = warp * 16 + g;
    #pragma unroll
    for (int nb = 2; nb < 7; nb++) {
      int c = (nb - 2) * 8 + 2 * t;
      st[lr * 41 + c] = acc[nb * 4]; st[lr * 41 + c + 1] = acc[nb * 4 + 1];
      st[(lr + 8) * 41 + c] = acc[nb * 4 + 2]; st[(lr + 8) * 41 + c + 1] = acc[nb * 4 + 3];
    }
    __syncthreads();
    float4* red = (float4*)(smem + 32768);
    const int row = tid & 127, key = rt * 128 + row;
    float v[18];
    if (tid < 128) {
      float n2 = 0.f;
      #pragma unroll
      for (int d = 0; d < 18; d++) { v[d] = bfr(st[row * 41 + d]); n2 += v[d] * v[d]; }
      const bool mufu = (KMASK >> ((key >> 3) & 7)) & 1;
      const float sc = mufu ? 32.f : 0.0625f;
      g_kv[key] = make_uint4(pack2h(v[0] * sc, v[1] * sc), pack2h(v[2] * sc, v[3] * sc), pack2h(v[4] * sc, v[5] * sc), pack2h(v[6] * sc, v[7] * sc));
      g_kv[SEQ + key] = make_uint4(pack2h(v[8] * sc, v[9] * sc), pack2h(v[10] * sc, v[11] * sc), pack2h(v[12] * sc, v[13] * sc), pack2h(v[14] * sc, v[15] * sc));
      g_kv[2 * SEQ + key] = make_uint4(pack2h(v[16] * sc, v[17] * sc), mufu ? 0x3C000000u : 0x00001800u, pack2h(bfr(st[row * 41 + 34]), bfr(st[row * 41 + 35])), 0x00003C00u);
      #pragma unroll
      for (int d = 0; d < 9; d++) *(float2*)(g_kraw + key * 18 + 2 * d) = make_float2(v[2 * d], v[2 * d + 1]);
      if (!(n2 <= 3e38f)) n2 = 3e38f;
      float r = st[row * 41 + 36]; int ri = key;
      #pragma unroll
      for (int o = 16; o; o >>= 1) {
        n2 = fmaxf(n2, __shfl_xor_sync(~0u, n2, o));
        float r2 = __shfl_xor_sync(~0u, r, o); int i2 = __shfl_xor_sync(~0u, ri, o);
        if (r2 > r || (r2 == r && i2 < ri)) { r = r2; ri = i2; }
      }
      if (lane == 0) red[warp] = make_float4(n2, 0.f, r, __int_as_float(ri));
    } else {
      float vm = 0.f;
      #pragma unroll
      for (int d = 0; d < 18; d++) { v[d] = bfr(st[row * 41 + 18 + d]); float a = fabsf(v[d]); vm = (a <= 3e38f) ? fmaxf(vm, a) : 3e38f; }
      g_kv[3 * SEQ + key] = make_uint4(pack2h(v[0], v[1]), pack2h(v[2], v[3]), pack2h(v[4], v[5]), pack2h(v[6], v[7]));
      g_kv[4 * SEQ + key] = make_uint4(pack2h(v[8], v[9]), pack2h(v[10], v[11]), pack2h(v[12], v[13]), pack2h(v[14], v[15]));
      #pragma unroll
      for (int d = 0; d < 9; d++) *(float2*)(g_vraw + key * 18 + 2 * d) = make_float2(v[2 * d], v[2 * d + 1]);
      g_gate[key] = 1.f / (1.f + __expf(-bfr(st[row * 41 + 37])));
      #pragma unroll
      for (int o = 16; o; o >>= 1) vm = fmaxf(vm, __shfl_xor_sync(~0u, vm, o));
      if (lane == 0) red[warp] = make_float4(0.f, vm, 0.f, 0.f);
    }
    __syncthreads();
    if (tid == 0) {
      float4 a = red[0];
      #pragma unroll
      for (int w = 1; w < 4; w++) { float4 b = red[w]; a.x = fmaxf(a.x, b.x); if (b.z > a.z) { a.z = b.z; a.w = b.w; } }
      a.y = fmaxf(fmaxf(red[4].y, red[5].y), fmaxf(red[6].y, red[7].y));
      g_stat[rt] = a;
    }
  }
}

__device__ __forceinline__ float4 load_stat(int lane) {
  uint4 u = ldg16c(&g_stat[lane & 15]);
  float k2 = __uint_as_float(u.x), vm = __uint_as_float(u.y), r = __uint_as_float(u.z); int ri = (int)u.w;
  #pragma unroll
  for (int o = 8; o; o >>= 1) {
    k2 = fmaxf(k2, __shfl_xor_sync(~0u, k2, o)); vm = fmaxf(vm, __shfl_xor_sync(~0u, vm, o));
    float r2 = __shfl_xor_sync(~0u, r, o); int i2 = __shfl_xor_sync(~0u, ri, o);
    if (r2 > r || (r2 == r && i2 < ri)) { r = r2; ri = i2; }
  }
  return make_float4(k2, vm, r, __int_as_float(ri & (SEQ - 1)));
}

__device__ __forceinline__ float sqrta(float x) { float r; asm("sqrt.approx.f32 %0, %1;" : "=f"(r) : "f"(x)); return r; }
__device__ __forceinline__ uint32_t ex2poly(uint32_t x) {
  uint32_t t = hfma2r(x, 0x02000200u, 0u);
  uint32_t u = hfma2(t, 0xF800F800u, x);
  uint32_t e = hfma2r(u, 0x47AC47ACu, 0x29A029A0u);
  uint32_t p = hfma2(e, u, 0x08000800u);
  return p + (t << 10);
}
__device__ __forceinline__ void softmax64(const uint32_t* s, uint32_t* p) {
  #pragma unroll
  for (int j = 0; j < 8; j++) {
    if ((KMASK >> j) & 1) { p[2*j] = ex2h2(s[2*j]); p[2*j+1] = ex2h2(s[2*j+1]); }
    else { p[2*j] = ex2poly(s[2*j]); p[2*j+1] = ex2poly(s[2*j+1]); }
  }
}
__device__ __forceinline__ void qk64(uint32_t* s, const uint32_t* q, uint32_t sb16, int key0) {
  uint32_t lo = (sb16 | ((PL >> 4) << 16)) + key0;
  wgh_n64_sd0(s, q[0], q[1], q[2], q[3], mk64(lo, 8));
  wgh_n64_sd1(s, q[4], q[5], 0, 0, mk64(lo + (2 * PL >> 4), 8));
}
__device__ __forceinline__ void pv64(float* o, const uint32_t* p, uint32_t sb16, int key0) {
  uint32_t lo = (sb16 | (8 << 16)) + (2 * PL >> 4) + key0;
  #pragma unroll
  for (int j = 0; j < 4; j++) wg_pv(o, p[4*j], p[4*j+1], p[4*j+2], p[4*j+3], mk64(lo + j * 16, PL >> 4));
}
__device__ __forceinline__ void attn_exact(int q0, int h, int lane) {
  #pragma unroll 1
  for (int r = 0; r < 16; r++) {
    float q[18], o[18];
    #pragma unroll
    for (int d = 0; d < 18; d++) { q[d] = __bfloat162float(g_q[(size_t)(q0 + r) * DM + h * 18 + d]) * 0.23570226f; o[d] = 0.f; }
    float m = -INFINITY;
    #pragma unroll 1
    for (int k = lane; k < SEQ; k += 32) {
      float s = 0.f;
      #pragma unroll
      for (int d = 0; d < 18; d++) s = fmaf(q[d], g_kraw[k * 18 + d], s);
      m = fmaxf(m, s);
    }
    #pragma unroll
    for (int x = 16; x; x >>= 1) m = fmaxf(m, __shfl_xor_sync(~0u, m, x));
    float l = 0.f;
    #pragma unroll 1
    for (int k = lane; k < SEQ; k += 32) {
      float s = 0.f;
      #pragma unroll
      for (int d = 0; d < 18; d++) s = fmaf(q[d], g_kraw[k * 18 + d], s);
      float p = __expf(s - m);
      l += p;
      #pragma unroll
      for (int d = 0; d < 18; d++) o[d] = fmaf(p, g_vraw[k * 18 + d], o[d]);
    }
    #pragma unroll
    for (int x = 16; x; x >>= 1) {
      l += __shfl_xor_sync(~0u, l, x);
      #pragma unroll
      for (int d = 0; d < 18; d++) o[d] += __shfl_xor_sync(~0u, o[d], x);
    }
    float inv = __fdividef(1.f, l), mine = 0.f;
    #pragma unroll
    for (int d = 0; d < 18; d++) if (lane == d) mine = o[d];
    if (lane < 18) g_o[(size_t)(q0 + r) * DM + h * 18 + lane] = __float2bfloat16(mine * inv);
  }
}

__device__ __forceinline__ void ffn_slice(int sl, int tid, int barid, float* sx, const __nv_bfloat16* __restrict__ x, const __nv_bfloat16* __restrict__ wgt,
    const __nv_bfloat16* __restrict__ wup, const __nv_bfloat16* __restrict__ wdn) {
  const int ch = tid & 7, rg = tid >> 3;
  const __nv_bfloat16* wp = (ch < 4 ? wgt : wup) + (size_t)rg * FF + sl * 32 + (ch & 3) * 8;
  const __nv_bfloat16* dp = wdn + (size_t)sl * 32 * DM;
  if ((ch & 3) == 0) {
    #pragma unroll 4
    for (int i = 0; i < 36; i++) asm volatile("prefetch.global.L2 [%0];" :: "l"(wp + (size_t)i * 16 * FF));
  }
  #pragma unroll
  for (int i = 0; i < 3; i++) if (tid + i * 128 < 288) asm volatile("prefetch.global.L2 [%0];" :: "l"(dp + (tid + i * 128) * 64));
  pdl_wait();
  const int idx = __float_as_int(load_stat(tid & 31).w);
  for (int i = tid; i < DM; i += 128) sx[i] = __bfloat162float(x[(size_t)idx * DM + i]);
  asm volatile("bar.sync %0, 128;" :: "r"(barid) : "memory");
  float acc[8];
  #pragma unroll
  for (int i = 0; i < 8; i++) acc[i] = 0.f;
  #pragma unroll 1
  for (int i = 0; i < 36; i += 2) {
    uint4 w0 = ldg16(wp + (size_t)i * 16 * FF), w1 = ldg16(wp + (size_t)(i + 1) * 16 * FF);
    float x0 = sx[rg + i * 16], x1 = sx[rg + i * 16 + 16];
    acc[0] = fmaf(x0, bflo(w0.x), acc[0]); acc[1] = fmaf(x0, bfhi(w0.x), acc[1]); acc[2] = fmaf(x0, bflo(w0.y), acc[2]); acc[3] = fmaf(x0, bfhi(w0.y), acc[3]);
    acc[4] = fmaf(x0, bflo(w0.z), acc[4]); acc[5] = fmaf(x0, bfhi(w0.z), acc[5]); acc[6] = fmaf(x0, bflo(w0.w), acc[6]); acc[7] = fmaf(x0, bfhi(w0.w), acc[7]);
    acc[0] = fmaf(x1, bflo(w1.x), acc[0]); acc[1] = fmaf(x1, bfhi(w1.x), acc[1]); acc[2] = fmaf(x1, bflo(w1.y), acc[2]); acc[3] = fmaf(x1, bfhi(w1.y), acc[3]);
    acc[4] = fmaf(x1, bflo(w1.z), acc[4]); acc[5] = fmaf(x1, bfhi(w1.z), acc[5]); acc[6] = fmaf(x1, bflo(w1.w), acc[6]); acc[7] = fmaf(x1, bfhi(w1.w), acc[7]);
  }
  #pragma unroll
  for (int i = 0; i < 8; i++) { acc[i] += __shfl_xor_sync(~0u, acc[i], 8); acc[i] += __shfl_xor_sync(~0u, acc[i], 16); }
  float* sr = sx + DM;
  if ((tid & 31) < 8) {
    #pragma unroll
    for (int i = 0; i < 8; i++) sr[(tid >> 5) * 64 + ch * 8 + i] = acc[i];
  }
  asm volatile("bar.sync %0, 128;" :: "r"(barid) : "memory");
  float* sh = sr + 256;
  if (tid < 32) {
    float gt = bfr(sr[tid] + sr[64 + tid] + sr[128 + tid] + sr[192 + tid]);
    float up = bfr(sr[32 + tid] + sr[96 + tid] + sr[160 + tid] + sr[224 + tid]);
    sh[tid] = bfr(bfr(__fdividef(gt, 1.f + __expf(-gt))) * up);
  }
  asm volatile("bar.sync %0, 128;" :: "r"(barid) : "memory");
  if (tid < 72) {
    #pragma unroll
    for (int i = 0; i < 8; i++) acc[i] = 0.f;
    #pragma unroll 1
    for (int i = 0; i < 32; i += 2) {
      uint4 w0 = ldg16(dp + i * DM + tid * 8), w1 = ldg16(dp + (i + 1) * DM + tid * 8);
      float x0 = sh[i], x1 = sh[i + 1];
      acc[0] = fmaf(x0, bflo(w0.x), acc[0]); acc[1] = fmaf(x0, bfhi(w0.x), acc[1]); acc[2] = fmaf(x0, bflo(w0.y), acc[2]); acc[3] = fmaf(x0, bfhi(w0.y), acc[3]);
      acc[4] = fmaf(x0, bflo(w0.z), acc[4]); acc[5] = fmaf(x0, bfhi(w0.z), acc[5]); acc[6] = fmaf(x0, bflo(w0.w), acc[6]); acc[7] = fmaf(x0, bfhi(w0.w), acc[7]);
      acc[0] = fmaf(x1, bflo(w1.x), acc[0]); acc[1] = fmaf(x1, bfhi(w1.x), acc[1]); acc[2] = fmaf(x1, bflo(w1.y), acc[2]); acc[3] = fmaf(x1, bfhi(w1.y), acc[3]);
      acc[4] = fmaf(x1, bflo(w1.z), acc[4]); acc[5] = fmaf(x1, bfhi(w1.z), acc[5]); acc[6] = fmaf(x1, bflo(w1.w), acc[6]); acc[7] = fmaf(x1, bfhi(w1.w), acc[7]);
    }
    float4* yp = (float4*)(g_ypart + sl * DM + tid * 8);
    yp[0] = make_float4(acc[0], acc[1], acc[2], acc[3]); yp[1] = make_float4(acc[4], acc[5], acc[6], acc[7]);
  }
}

constexpr int K2_SMEM = 5 * PL + 64 + 4096 + 7 * 2048;
__global__ void __launch_bounds__(640, 1) k_attn(const __nv_bfloat16* __restrict__ x, const __nv_bfloat16* __restrict__ wgt, const __nv_bfloat16* __restrict__ wup,
    const __nv_bfloat16* __restrict__ wdn, const __nv_bfloat16* __restrict__ wo) {
  extern __shared__ __align__(1024) uint8_t smem[];
  const uint32_t sbase = (uint32_t)__cvta_generic_to_shared(smem);
  const uint32_t bars = sbase + 5 * PL;
  const int wg = __shfl_sync(0xffffffffu, threadIdx.x >> 7, 0);
  if (threadIdx.x == 0) {
    #pragma unroll
    for (int i = 0; i < 8; i++) asm volatile("mbarrier.init.shared::cta.b64 [%0], 1;" :: "r"(bars + i * 8) : "memory");
    asm volatile("fence.mbarrier_init.release.cluster;" ::: "memory");
    proxy_fence();
  }
  __syncthreads();
  if (wg == 4) {
    asm volatile("setmaxnreg.dec.sync.aligned.u32 32;");
    const int tid = threadIdx.x - 512;
    if (blockIdx.x < 128) {
      if (tid == 0) {
        pdl_wait();
        #pragma unroll 1
        for (int c = 0; c < 8; c++) {
          asm volatile("mbarrier.arrive.expect_tx.shared::cta.b64 _, [%0], %1;" :: "r"(bars + c * 8), "r"(5 * 4096) : "memory");
          #pragma unroll
          for (int p = 0; p < 5; p++)
            asm volatile("cp.async.bulk.shared::cluster.global.mbarrier::complete_tx::bytes [%0], [%1], %2, [%3];"
              :: "r"(sbase + p * PL + c * 4096), "l"(g_kv + p * SEQ + c * 256), "r"(4096), "r"(bars + c * 8) : "memory");
        }
        pdl_go();
      }
      __syncwarp();
      if (tid < 41 && blockIdx.x * 41 + tid < 5184) asm volatile("prefetch.global.L2 [%0];" :: "l"(wo + (blockIdx.x * 41 + tid) * 64));
      ffn_slice(blockIdx.x, tid, 1, (float*)(smem + 5 * PL + 64), x, wgt, wup, wdn);
    }
  } else {
    asm volatile("setmaxnreg.inc.sync.aligned.u32 112;");
    if (blockIdx.x >= 128) {
      ffn_slice(128 + (blockIdx.x - 128) * 4 + wg, threadIdx.x & 127, 2 + wg, (float*)(smem + wg * 4096), x, wgt, wup, wdn);
    } else {
      const uint32_t sb = sbase >> 4;
      const int warp = (threadIdx.x >> 5) & 3, lane = threadIdx.x & 31, g = lane >> 2, t = lane & 3;
      const int q0 = blockIdx.x * 16;
      pdl_wait();
      uint32_t qall[2][6];
      uint32_t flags = 0;
      {
        uint32_t raw[2][6];
        #pragma unroll
        for (int i = 0; i < 2; i++) {
          const int h = (wg + i * 4) * 4 + warp;
          const uint32_t* qp0 = (const uint32_t*)(g_q + (size_t)(q0 + g) * DM + h * 18);
          const uint32_t* qp1 = qp0 + 4 * DM;
          raw[i][0] = __ldcg(qp0 + t); raw[i][1] = __ldcg(qp1 + t); raw[i][2] = __ldcg(qp0 + t + 4); raw[i][3] = __ldcg(qp1 + t + 4);
          raw[i][4] = t == 0 ? __ldcg(qp0 + 8) : 0u; raw[i][5] = t == 0 ? __ldcg(qp1 + 8) : 0u;
        }
        const float4 st = load_stat(lane);
        const bool kvbad = !(st.x <= 65536.f) || !(st.y <= 16384.f) || !(st.y >= 0.015625f);
        const float QS = 0.23570226f * 1.44269504f, kn = sqrta(st.x) * (QS * 1.01f * 8.f);
        #pragma unroll
        for (int i = 0; i < 2; i++) {
          float n[2] = {0.f, 0.f};
          #pragma unroll
          for (int j = 0; j < 6; j++) {
            float a = bflo(raw[i][j]), b = bfhi(raw[i][j]);
            n[j & 1] += a * a + b * b;
            qall[i][j] = pack2h(a * (QS / 32.f), b * (QS / 32.f));
          }
          #pragma unroll
          for (int r = 0; r < 2; r++) {
            n[r] += __shfl_xor_sync(~0u, n[r], 1); n[r] += __shfl_xor_sync(~0u, n[r], 2);
            float M = ceilf(sqrta(n[r]) * kn) * 0.125f;
            bool bad = kvbad || !(n[r] <= 65536.f) || !(M <= 40.f);
            if (bad) { flags |= 1u << i; M = 0.f; }
            if (M > 14.f) { flags |= 4u << (2 * i + r); M = 28.f - M; }
            if (t == 1) qall[i][4 + r] = pack2h(M, M - 13.f);
          }
        }
      }
      volatile uint32_t* stash = (volatile uint32_t*)(smem + 5 * PL + 64 + 4096) + threadIdx.x;
      #pragma unroll
      for (int j = 0; j < 6; j++) stash[j * 512] = qall[1][j];
      stash[6 * 512] = flags;
      #pragma unroll
      for (int i = 0; i < 2; i++) {
        const int h = (wg + i * 4) * 4 + warp;
        uint32_t* qa = qall[0];
        if (i == 1) {
          #pragma unroll
          for (int j = 0; j < 6; j++) qa[j] = stash[j * 512];
        }
        float o[12];
        #pragma unroll
        for (int k = 0; k < 12; k++) asm volatile("mov.b32 %0, 0;" : "=f"(o[k]));
        uint32_t s0[16], s1[16], p0[16], p1[16];
        if (i == 0) mbar_wait(bars, 0);
        wg_fence(); qk64(s0, qa, sb, 0); wg_commit(); wg_wait<0>(); fence_regs<16>(s0);
        #pragma unroll 1
        for (int j = 0; j < 32; j += 2) {
          if (i == 0 && (j & 2)) mbar_wait(bars + (((j + 2) & 31) << 1), 0);
          wg_fence();
          qk64(s1, qa, sb, (j + 1) * 64); wg_commit();
          softmax64(s0, p0);
          wg_fence();
          pv64(o, p0, sb, j * 64); wg_commit();
          wg_wait<1>();
          fence_regs<16>(s1);
          wg_fence();
          qk64(s0, qa, sb, ((j + 2) & 31) * 64); wg_commit();
          softmax64(s1, p1);
          wg_fence();
          pv64(o, p1, sb, (j + 1) * 64); wg_commit();
          wg_wait<1>();
          fence_regs<16>(s0);
        }
        wg_wait<0>();
        fence_regs<12>(o); fence_regs<16>(s0);
        flags = stash[6 * 512];
        float l0 = __shfl_sync(0xffffffffu, o[0], lane | 3), l1 = __shfl_sync(0xffffffffu, o[2], lane | 3);
        bool bad = ((flags >> i) & 1) || !(l0 <= 3e38f) || !(l1 <= 3e38f) || !(l0 > 0.f) || !(l1 > 0.f)
                   || (((flags >> (2 + 2 * i)) & 1) && l0 < 256.f) || (((flags >> (3 + 2 * i)) & 1) && l1 < 256.f);
        if (__any_sync(0xffffffffu, bad)) stash[6 * 512] = flags | (64u << i);
        else {
          float r0 = __fdividef(1.f, l0), r1 = __fdividef(1.f, l1);
          uint32_t* op0 = (uint32_t*)(g_o + (size_t)(q0 + g) * DM + h * 18);
          uint32_t* op1 = op0 + 4 * DM;
          op0[t] = pack2(o[4] * r0, o[5] * r0); op1[t] = pack2(o[6] * r1, o[7] * r1);
          op0[t + 4] = pack2(o[8] * r0, o[9] * r0); op1[t + 4] = pack2(o[10] * r1, o[11] * r1);
          if (t == 2) { op0[8] = pack2(o[0] * r0, o[1] * r0); op1[8] = pack2(o[2] * r1, o[3] * r1); }
        }
      }
      flags = stash[6 * 512];
      #pragma unroll 1
      for (int i = 0; i < 2; i++) if ((flags >> (6 + i)) & 1) attn_exact(q0, (wg + i * 4) * 4 + warp, lane);
    }
  }
}
constexpr int K3_SMEM = 9 * BPS + NSL * 72 * 4 + 1024;
__global__ void __launch_bounds__(256, 1) k_out(const __nv_bfloat16* __restrict__ x, const __nv_bfloat16* __restrict__ wo, __nv_bfloat16* __restrict__ out) {
  extern __shared__ __align__(1024) uint8_t smem[];
  const int tid = threadIdx.x, lane = tid & 31, g = lane >> 2, t = lane & 3, warp = tid >> 5;
  const int rt = blockIdx.x >> 3, ct = blockIdx.x & 7;
  const uint32_t sb = (uint32_t)__cvta_generic_to_shared(smem);
  const int r0 = rt * 128 + warp * 16 + g;
  #pragma unroll
  for (int c = 0; c < 3; c++) { loadB<9>(sb, wo + ct * 72, c * 192, tid); cp_commit(); }
  uint32_t xr[18];
  const uint32_t* xp = (const uint32_t*)(x + (size_t)r0 * DM + ct * 72) + t;
  #pragma unroll
  for (int nb = 0; nb < 9; nb++) { xr[2 * nb] = __ldg(xp + nb * 4); xr[2 * nb + 1] = __ldg(xp + 4 * DM + nb * 4); }
  pdl_wait();
  const __nv_bfloat16* a0p = g_o + (size_t)r0 * DM + t * 8;
  uint4 va[18], vb[18];
  #pragma unroll
  for (int b = 0; b < 18; b++) { va[b] = ldg16c(a0p + b * 32); vb[b] = ldg16c(a0p + 8 * DM + b * 32); }
  const float4 st = load_stat(lane);
  const int idx = __float_as_int(st.w);
  const float g0 = __ldcg(g_gate + r0), g1 = __ldcg(g_gate + r0 + 8);
  const bool has = (idx >> 7) == rt;
  float* yp = (float*)(smem + 9 * BPS + 16 * 7);
  if (has) {
    for (int id = tid; id < NSL * 18; id += 256) { int s = id / 18, c = id % 18; cp16(sb + 9 * BPS + 112 + id * 16, g_ypart + s * DM + ct * 72 + c * 4); }
  }
  cp_commit();
  float acc[36];
  #pragma unroll
  for (int i = 0; i < 36; i++) asm volatile("mov.b32 %0, 0;" : "=f"(acc[i]));
  const uint32_t dlo = (sb >> 4) | (8 << 16);
  cp_wait<1>();
  proxy_fence();
  __syncthreads();
  #pragma unroll
  for (int c = 0; c < 3; c++) {
    wg_fence();
    #pragma unroll
    for (int b = c * 6; b < c * 6 + 6; b++) {
      wg_n72(acc, va[b].x, vb[b].x, va[b].y, vb[b].y, mk64(dlo + b * 32, BPS >> 4));
      wg_n72(acc, va[b].z, vb[b].z, va[b].w, vb[b].w, mk64(dlo + b * 32 + 16, BPS >> 4));
    }
    wg_commit();
  }
  float* ys = yp + NSL * 72;
  if (has) {
    cp_wait<0>();
    __syncthreads();
    if (tid < 216) {
      int c = tid % 72, p = tid / 72; float s = 0.f;
      #pragma unroll 8
      for (int i = p * 48; i < p * 48 + 48; i++) s += yp[i * 72 + c];
      ys[tid] = s;
    }
    __syncthreads();
  }
  wg_wait<0>();
  fence_regs<36>(acc);
  uint32_t* op = (uint32_t*)(out + (size_t)r0 * DM + ct * 72) + t;
  const float rs = bfr(1.f / (1.f + __expf(-bfr(st.z))));
  #pragma unroll
  for (int nb = 0; nb < 9; nb++) {
    float b0 = bflo(xr[2 * nb]), b1 = bfhi(xr[2 * nb]), b2 = bflo(xr[2 * nb + 1]), b3 = bfhi(xr[2 * nb + 1]);
    if (has && (idx == r0 || idx == r0 + 8)) {
      int c = nb * 8 + 2 * t;
      float y0 = bfr(bfr(ys[c] + ys[72 + c] + ys[144 + c]) * rs), y1 = bfr(bfr(ys[c + 1] + ys[73 + c] + ys[145 + c]) * rs);
      if (idx == r0) { b0 += y0; b1 += y1; } else { b2 += y0; b3 += y1; }
    }
    op[nb * 4] = pack2(fmaf(g0, acc[nb * 4] - b0, b0), fmaf(g0, acc[nb * 4 + 1] - b1, b1));
    op[4 * DM + nb * 4] = pack2(fmaf(g1, acc[nb * 4 + 2] - b2, b2), fmaf(g1, acc[nb * 4 + 3] - b3, b3));
  }
}

extern "C" void kernel_launch(void* const* d_in, const int* in_sizes, int n_in, void* d_out, int out_size) {
  typedef const __nv_bfloat16* P;
  P x = (P)d_in[0], wq = (P)d_in[1], wk = (P)d_in[2], wv = (P)d_in[3], wo = (P)d_in[4], wr = (P)d_in[6], wgt = (P)d_in[7], wup = (P)d_in[8], wdn = (P)d_in[9], gw = (P)d_in[10];
  static bool init = false;
  if (!init) {
    cudaFuncSetAttribute(k_proj, cudaFuncAttributeMaxDynamicSharedMemorySize, 10 * BPS);
    cudaFuncSetAttribute(k_attn, cudaFuncAttributeMaxDynamicSharedMemorySize, K2_SMEM);
    cudaFuncSetAttribute(k_out, cudaFuncAttributeMaxDynamicSharedMemorySize, K3_SMEM);
    init = true;
  }
  cudaStream_t s = cudaStreamPerThread;
  k_proj<<<128, 256, 10 * BPS, s>>>(x, wq, wk, wv, wr, gw);
  cudaLaunchAttribute at[1];
  at[0].id = cudaLaunchAttributeProgrammaticStreamSerialization; at[0].val.programmaticStreamSerializationAllowed = 1;
  cudaLaunchConfig_t cfg = {};
  cfg.stream = s; cfg.attrs = at; cfg.numAttrs = 1;
  cfg.gridDim = dim3(132); cfg.blockDim = dim3(640); cfg.dynamicSmemBytes = K2_SMEM;
  cudaLaunchKernelEx(&cfg, k_attn, x, wgt, wup, wdn, wo);
  cfg.gridDim = dim3(128); cfg.blockDim = dim3(256); cfg.dynamicSmemBytes = K3_SMEM;
  cudaLaunchKernelEx(&cfg, k_out, x, wo, (__nv_bfloat16*)d_out);
}
```

```cpp
#include <cuda_runtime.h>
#include <cuda_bf16.h>
#include <cuda_fp16.h>
#include <stdint.h>
#include <cuda.h>

constexpr int SEQ = 2048, DM = 576, FF = 4608, NSL = 144;
constexpr uint32_t PL = 32768;
constexpr uint32_t KMASK = 0x25;

__device__ __align__(128) __nv_bfloat16 g_q[SEQ * DM];
__device__ __align__(128) __nv_bfloat16 g_o[SEQ * DM];
__device__ uint4 g_kv[5 * SEQ];
__device__ float g_kraw[SEQ * 18];
__device__ float g_vraw[SEQ * 18];
__device__ float g_gate[SEQ];
__device__ float4 g_stat[16];
__device__ float g_ypart[NSL * DM];

#define STAMP(k)
#define STAMP0(k)
__device__ __forceinline__ void wgh_n64_sd0(uint32_t* d, uint32_t a0, uint32_t a1, uint32_t a2, uint32_t a3, uint64_t bdesc) {
  asm volatile("{\n.reg .pred p;\nsetp.ne.b32 p, 0, 0;\n"
    "wgmma.mma_async.sync.aligned.m64n64k16.f16.f16.f16 {%0, %1, %2, %3, %4, %5, %6, %7, %8, %9, %10, %11, %12, %13, %14, %15}, {%16, %17, %18, %19}, %20, p, 1, 1, 0;\n}\n"
    : "=r"(d[0]), "=r"(d[1]), "=r"(d[2]), "=r"(d[3]), "=r"(d[4]), "=r"(d[5]), "=r"(d[6]), "=r"(d[7]), "=r"(d[8]), "=r"(d[9]), "=r"(d[10]), "=r"(d[11]), "=r"(d[12]), "=r"(d[13]), "=r"(d[14]), "=r"(d[15]) : "r"(a0), "r"(a1), "r"(a2), "r"(a3), "l"(bdesc));
}
__device__ __forceinline__ void wgh_n64_sd1(uint32_t* d, uint32_t a0, uint32_t a1, uint32_t a2, uint32_t a3, uint64_t bdesc) {
  asm volatile("{\n.reg .pred p;\nsetp.ne.b32 p, 1, 0;\n"
    "wgmma.mma_async.sync.aligned.m64n64k16.f16.f16.f16 {%0, %1, %2, %3, %4, %5, %6, %7, %8, %9, %10, %11, %12, %13, %14, %15}, {%16, %17, %18, %19}, %20, p, 1, 1, 0;\n}\n"
    : "+r"(d[0]), "+r"(d[1]), "+r"(d[2]), "+r"(d[3]), "+r"(d[4]), "+r"(d[5]), "+r"(d[6]), "+r"(d[7]), "+r"(d[8]), "+r"(d[9]), "+r"(d[10]), "+r"(d[11]), "+r"(d[12]), "+r"(d[13]), "+r"(d[14]), "+r"(d[15]) : "r"(a0), "r"(a1), "r"(a2), "r"(a3), "l"(bdesc));
}
__device__ __forceinline__ void wg_pv(float* d, uint32_t a0, uint32_t a1, uint32_t a2, uint32_t a3, uint64_t bdesc) {
  asm volatile("{\n.reg .pred p;\nsetp.ne.b32 p, 1, 0;\n"
    "wgmma.mma_async.sync.aligned.m64n24k16.f32.f16.f16 {%0, %1, %2, %3, %4, %5, %6, %7, %8, %9, %10, %11}, {%12, %13, %14, %15}, %16, p, 1, 1, 1;\n}\n"
    : "+f"(d[0]), "+f"(d[1]), "+f"(d[2]), "+f"(d[3]), "+f"(d[4]), "+f"(d[5]), "+f"(d[6]), "+f"(d[7]), "+f"(d[8]), "+f"(d[9]), "+f"(d[10]), "+f"(d[11]) : "r"(a0), "r"(a1), "r"(a2), "r"(a3), "l"(bdesc));
}
__device__ __forceinline__ void wg_ss160(float* d, uint64_t adesc, uint64_t bdesc) {
  asm volatile("{\n.reg .pred p;\nsetp.ne.b32 p, 1, 0;\n"
    "wgmma.mma_async.sync.aligned.m64n160k16.f32.bf16.bf16 {%0, %1, %2, %3, %4, %5, %6, %7, %8, %9, %10, %11, %12, %13, %14, %15, %16, %17, %18, %19, %20, %21, %22, %23, %24, %25, %26, %27, %28, %29, %30, %31, %32, %33, %34, %35, %36, %37, %38, %39, %40, %41, %42, %43, %44, %45, %46, %47, %48, %49, %50, %51, %52, %53, %54, %55, %56, %57, %58, %59, %60, %61, %62, %63, %64, %65, %66, %67, %68, %69, %70, %71, %72, %73, %74, %75, %76, %77, %78, %79}, %80, %81, p, 1, 1, 1, 0;\n}\n"
    : "+f"(d[0]), "+f"(d[1]), "+f"(d[2]), "+f"(d[3]), "+f"(d[4]), "+f"(d[5]), "+f"(d[6]), "+f"(d[7]), "+f"(d[8]), "+f"(d[9]), "+f"(d[10]), "+f"(d[11]), "+f"(d[12]), "+f"(d[13]), "+f"(d[14]), "+f"(d[15]), "+f"(d[16]), "+f"(d[17]), "+f"(d[18]), "+f"(d[19]), "+f"(d[20]), "+f"(d[21]), "+f"(d[22]), "+f"(d[23]), "+f"(d[24]), "+f"(d[25]), "+f"(d[26]), "+f"(d[27]), "+f"(d[28]), "+f"(d[29]), "+f"(d[30]), "+f"(d[31]), "+f"(d[32]), "+f"(d[33]), "+f"(d[34]), "+f"(d[35]), "+f"(d[36]), "+f"(d[37]), "+f"(d[38]), "+f"(d[39]), "+f"(d[40]), "+f"(d[41]), "+f"(d[42]), "+f"(d[43]), "+f"(d[44]), "+f"(d[45]), "+f"(d[46]), "+f"(d[47]), "+f"(d[48]), "+f"(d[49]), "+f"(d[50]), "+f"(d[51]), "+f"(d[52]), "+f"(d[53]), "+f"(d[54]), "+f"(d[55]), "+f"(d[56]), "+f"(d[57]), "+f"(d[58]), "+f"(d[59]), "+f"(d[60]), "+f"(d[61]), "+f"(d[62]), "+f"(d[63]), "+f"(d[64]), "+f"(d[65]), "+f"(d[66]), "+f"(d[67]), "+f"(d[68]), "+f"(d[69]), "+f"(d[70]), "+f"(d[71]), "+f"(d[72]), "+f"(d[73]), "+f"(d[74]), "+f"(d[75]), "+f"(d[76]), "+f"(d[77]), "+f"(d[78]), "+f"(d[79]) : "l"(adesc), "l"(bdesc));
}

__device__ __forceinline__ void wg_fence() { asm volatile("wgmma.fence.sync.aligned;" ::: "memory"); }
__device__ __forceinline__ void wg_commit() { asm volatile("wgmma.commit_group.sync.aligned;" ::: "memory"); }
template<int N> __device__ __forceinline__ void wg_wait() { asm volatile("wgmma.wait_group.sync.aligned %0;" :: "n"(N) : "memory"); }
__device__ __forceinline__ uint32_t pack2(float lo, float hi) { uint32_t r; asm("cvt.rn.bf16x2.f32 %0, %1, %2;" : "=r"(r) : "f"(hi), "f"(lo)); return r; }
__device__ __forceinline__ uint32_t pack2h(float lo, float hi) { uint32_t r; asm("cvt.rn.f16x2.f32 %0, %1, %2;" : "=r"(r) : "f"(hi), "f"(lo)); return r; }
__device__ __forceinline__ float bflo(uint32_t v) { return __uint_as_float(v << 16); }
__device__ __forceinline__ float bfhi(uint32_t v) { return __uint_as_float(v & 0xffff0000u); }
__device__ __forceinline__ float bfr(float v) { return __bfloat162float(__float2bfloat16(v)); }
__device__ __forceinline__ uint32_t hfma2(uint32_t a, uint32_t b, uint32_t c) { uint32_t r; asm("fma.rn.f16x2 %0, %1, %2, %3;" : "=r"(r) : "r"(a), "r"(b), "r"(c)); return r; }
__device__ __forceinline__ uint32_t hfma2r(uint32_t a, uint32_t b, uint32_t c) { uint32_t r; asm("fma.rn.relu.f16x2 %0, %1, %2, %3;" : "=r"(r) : "r"(a), "r"(b), "r"(c)); return r; }
__device__ __forceinline__ uint32_t ex2h2(uint32_t x) { uint32_t r; asm("ex2.approx.f16x2 %0, %1;" : "=r"(r) : "r"(x)); return r; }
__device__ __forceinline__ uint64_t mk64(uint32_t lo, uint32_t hi) { uint64_t d; asm("mov.b64 %0, {%1, %2};" : "=l"(d) : "r"(lo), "r"(hi)); return d; }
template<int N> __device__ __forceinline__ void fence_regs(float* r) {
  #pragma unroll
  for (int i = 0; i < N; i++) asm volatile("" : "+f"(r[i]) :: "memory");
}
template<int N> __device__ __forceinline__ void fence_regs(uint32_t* r) {
  #pragma unroll
  for (int i = 0; i < N; i++) asm volatile("" : "+r"(r[i]) :: "memory");
}
__device__ __forceinline__ void cp16(uint32_t dst, const void* src) { asm volatile("cp.async.cg.shared.global [%0], [%1], 16;" :: "r"(dst), "l"(src) : "memory"); }
__device__ __forceinline__ void cp4(uint32_t dst, const void* src) { asm volatile("cp.async.ca.shared.global [%0], [%1], 4;" :: "r"(dst), "l"(src) : "memory"); }
__device__ __forceinline__ void cp_commit() { asm volatile("cp.async.commit_group;" ::: "memory"); }
template<int N> __device__ __forceinline__ void cp_wait() { asm volatile("cp.async.wait_group %0;" :: "n"(N) : "memory"); }
__device__ __forceinline__ void proxy_fence() { asm volatile("fence.proxy.async.shared::cta;" ::: "memory"); }
__device__ __forceinline__ void pdl_wait() { asm volatile("griddepcontrol.wait;" ::: "memory"); }
__device__ __forceinline__ void pdl_go() { asm volatile("griddepcontrol.launch_dependents;" ::: "memory"); }
__device__ __forceinline__ uint4 ldg16(const void* p) { uint4 v; asm volatile("ld.global.nc.L1::no_allocate.v4.u32 {%0,%1,%2,%3}, [%4];" : "=r"(v.x), "=r"(v.y), "=r"(v.z), "=r"(v.w) : "l"(p)); return v; }
__device__ __forceinline__ uint4 ldg16c(const void* p) { uint4 v; asm volatile("ld.global.L1::no_allocate.v4.u32 {%0,%1,%2,%3}, [%4];" : "=r"(v.x), "=r"(v.y), "=r"(v.z), "=r"(v.w) : "l"(p) : "memory"); return v; }
__device__ __forceinline__ void mbar_wait(uint32_t bar, uint32_t parity) {
  #pragma unroll 1
  for (int it = 0; it < (1 << 22); it++) {
    uint32_t ok;
    asm volatile("{\n.reg .pred p;\nmbarrier.try_wait.parity.shared::cta.b64 p, [%1], %2;\nselp.u32 %0, 1, 0, p;\n}\n" : "=r"(ok) : "r"(bar), "r"(parity) : "memory");
    if (ok) break;
  }
}
__device__ __forceinline__ void mbar_init(uint32_t bar, uint32_t cnt) { asm volatile("mbarrier.init.shared::cta.b64 [%0], %1;" :: "r"(bar), "r"(cnt) : "memory"); }
__device__ __forceinline__ void mbar_expect(uint32_t bar, uint32_t bytes) { asm volatile("mbarrier.arrive.expect_tx.shared::cta.b64 _, [%0], %1;" :: "r"(bar), "r"(bytes) : "memory"); }
__device__ __forceinline__ void mbar_arrive(uint32_t bar) { asm volatile("mbarrier.arrive.shared::cta.b64 _, [%0];" :: "r"(bar) : "memory"); }
__device__ __forceinline__ void tma_ld(uint32_t dst, const CUtensorMap* m, int c0, int c1, uint32_t bar) {
  asm volatile("cp.async.bulk.tensor.2d.shared::cluster.global.mbarrier::complete_tx::bytes [%0], [%1, {%3, %4}], [%2];" :: "r"(dst), "l"(m), "r"(bar), "r"(c0), "r"(c1) : "memory");
}
__device__ __forceinline__ void tma_ld_mc(uint32_t dst, const CUtensorMap* m, int c0, int c1, uint32_t bar, uint16_t mask) {
  asm volatile("cp.async.bulk.tensor.2d.shared::cluster.global.mbarrier::complete_tx::bytes.multicast::cluster [%0], [%1, {%3, %4}], [%2], %5;" :: "r"(dst), "l"(m), "r"(bar), "r"(c0), "r"(c1), "h"(mask) : "memory");
}
__device__ __forceinline__ void tma_st(const CUtensorMap* m, uint32_t src, int c0, int c1) {
  asm volatile("cp.async.bulk.tensor.2d.global.shared::cta.bulk_group [%0, {%2, %3}], [%1];" :: "l"(m), "r"(src), "r"(c0), "r"(c1) : "memory");
}
__device__ __forceinline__ void cluster_sync() { asm volatile("barrier.cluster.arrive.release.aligned;\nbarrier.cluster.wait.acquire.aligned;" ::: "memory"); }
__device__ __forceinline__ void bar_sync(int id, int n) { asm volatile("bar.sync %0, %1;" :: "r"(id), "r"(n) : "memory"); }
__device__ __forceinline__ void stsm4t(uint32_t a, uint32_t r0, uint32_t r1, uint32_t r2, uint32_t r3) {
  asm volatile("stmatrix.sync.aligned.m8n8.x4.trans.shared.b16 [%0], {%1,%2,%3,%4};" :: "r"(a), "r"(r0), "r"(r1), "r"(r2), "r"(r3) : "memory");
}
__device__ __forceinline__ void ldsm4t(uint32_t a, uint32_t* r) {
  asm volatile("ldmatrix.sync.aligned.m8n8.x4.trans.shared.b16 {%0,%1,%2,%3}, [%4];" : "=r"(r[0]), "=r"(r[1]), "=r"(r[2]), "=r"(r[3]) : "r"(a) : "memory");
}

constexpr int BN = 160, NTT = 13;
constexpr uint32_t G_A = 0, G_B = 9 * 8192, G_SLOT = BN * 128, G_BAR = G_B + 7 * G_SLOT, G_MISC = G_BAR + 256, G_SMEM = G_MISC + 2048;
__device__ __forceinline__ void gemm_init(uint32_t sb) {
  if (threadIdx.x == 0) {
    #pragma unroll
    for (int i = 0; i < 10; i++) mbar_init(sb + G_BAR + i * 8, 1);
    #pragma unroll
    for (int i = 0; i < 3; i++) mbar_init(sb + G_BAR + 128 + i * 8, 4);
    asm volatile("fence.mbarrier_init.release.cluster;" ::: "memory");
  }
  cluster_sync();
}
__device__ __forceinline__ void gemm_load_b(uint32_t sb, const CUtensorMap* mb, int nt, int rank, bool tail) {
  #pragma unroll 1
  for (int c = 0; c < 7; c++) tma_ld_mc(sb + G_B + c * G_SLOT + rank * 10240, mb, c * 64, nt * BN + rank * 80, sb + G_BAR + c * 8, 3);
  if (tail) {
    #pragma unroll 1
    for (int c = 7; c < 9; c++) {
      mbar_wait(sb + G_BAR + 128 + (c - 7) * 8, 0);
      tma_ld(sb + G_B + (c - 7) * G_SLOT, mb, c * 64, nt * BN, sb + G_BAR + c * 8);
      tma_ld(sb + G_B + (c - 7) * G_SLOT + 10240, mb, c * 64, nt * BN + 80, sb + G_BAR + c * 8);
    }
  }
}
__device__ __forceinline__ void gemm_main(uint32_t sb, float* acc) {
  #pragma unroll
  for (int i = 0; i < 80; i++) asm volatile("mov.b32 %0, 0;" : "=f"(acc[i]));
  const uint32_t hi = 64u | (1u << 30);
  const uint32_t alo = ((sb + G_A) >> 4) | (64u << 16), blo = ((sb + G_B) >> 4) | (1u << 16);
  #pragma unroll
  for (int c = 0; c < 9; c++) {
    mbar_wait(sb + G_BAR + c * 8, 0);
    wg_fence();
    #pragma unroll
    for (int k = 0; k < 4; k++) wg_ss160(acc, mk64(alo + c * 512 + k * 128, hi), mk64(blo + (c < 7 ? c : c - 7) * (G_SLOT >> 4) + k * 2, hi));
    wg_commit();
    if (c >= 1 && c <= 3) { wg_wait<1>(); if ((threadIdx.x & 31) == 0) mbar_arrive(sb + G_BAR + 128 + (c - 1) * 8); }
  }
  wg_wait<0>();
  fence_regs<80>(acc);
}

__global__ void __launch_bounds__(384, 1) k_proj(const __grid_constant__ CUtensorMap mx, const __grid_constant__ CUtensorMap mwq, const __grid_constant__ CUtensorMap mq,
    const __nv_bfloat16* __restrict__ wk, const __nv_bfloat16* __restrict__ wv, const __nv_bfloat16* __restrict__ wr, const __nv_bfloat16* __restrict__ gw) {
  extern __shared__ __align__(1024) uint8_t smem[];
  pdl_go();
  STAMP0(0);
  const int tid = threadIdx.x, lane = tid & 31, g = lane >> 2, t = lane & 3, warp = tid >> 5;
  const int mt = blockIdx.x, nt = blockIdx.y;
  const uint32_t sb = (uint32_t)__cvta_generic_to_shared(smem);
  gemm_init(sb);
  if (mt == 9) {
    #pragma unroll 3
    for (int id = tid; id < 576 * 18; id += 384) {
      int half = id >= 576 * 9, w = id - half * 576 * 9, k = w / 9, m = 2 * (w % 9) + half * 18;
      cp4(sb + G_A + k * 128 + (((m >> 3) ^ (k & 7)) << 4) + (m & 7) * 2, (half ? wv : wk) + 2 * w);
    }
    cp_commit();
  }
  if (tid == 128) {
    #pragma unroll 1
    for (int c = 0; c < 9; c++) {
      mbar_expect(sb + G_BAR + c * 8, mt == 9 ? G_SLOT : G_SLOT + 8192);
      if (mt < 9) tma_ld(sb + G_A + c * 8192, &mwq, mt * 64, c * 64, sb + G_BAR + c * 8);
      if (c < 7) tma_ld_mc(sb + G_B + c * G_SLOT + (mt & 1) * 10240, &mx, c * 64, nt * BN + (mt & 1) * 80, sb + G_BAR + c * 8, 3);
    }
  }
  if (mt == 9) {
    for (int k = tid; k < 576; k += 384)
      *(uint32_t*)(smem + G_A + k * 128 + ((4 ^ (k & 7)) << 4) + 8) = (uint32_t)__bfloat16_as_ushort(wr[k]) | ((uint32_t)__bfloat16_as_ushort(gw[k]) << 16);
    cp_wait<0>();
    proxy_fence();
    __syncthreads();
  }
  if (tid == 128) {
    #pragma unroll 1
    for (int c = 7; c < 9; c++) {
      mbar_wait(sb + G_BAR + 128 + (c - 7) * 8, 0);
      tma_ld(sb + G_B + (c - 7) * G_SLOT, &mx, c * 64, nt * BN, sb + G_BAR + c * 8);
      tma_ld(sb + G_B + (c - 7) * G_SLOT + 10240, &mx, c * 64, nt * BN + 80, sb + G_BAR + c * 8);
    }
  }
  float* st = (float*)(smem + G_B + 2 * G_SLOT);
  if (warp < 4) {
    float acc[80];
    gemm_main(sb, acc);
    STAMP0(4);
    if (mt < 9) {
      const uint32_t ob = sb + G_B + 2 * G_SLOT + ((lane >> 4) * 8 + (lane & 7)) * 128 + (((2 * warp + ((lane >> 3) & 1)) ^ (lane & 7)) << 4);
      bar_sync(1, 128);
      #pragma unroll
      for (int j = 0; j < 20; j += 2)
        stsm4t(ob + j * 1024, pack2(acc[4*j], acc[4*j+1]), pack2(acc[4*j+2], acc[4*j+3]), pack2(acc[4*j+4], acc[4*j+5]), pack2(acc[4*j+6], acc[4*j+7]));
      proxy_fence();
      bar_sync(1, 128);
      if (tid == 0) {
        tma_st(&mq, sb + G_B + 2 * G_SLOT, mt * 64, nt * BN);
        tma_st(&mq, sb + G_B + 2 * G_SLOT + 10240, mt * 64, nt * BN + 80);
        asm volatile("cp.async.bulk.commit_group;\ncp.async.bulk.wait_group 0;" ::: "memory");
      }
    } else {
      bar_sync(1, 128);
      if (warp < 3) {
        #pragma unroll
        for (int j = 0; j < 20; j++) {
          float* p = st + (8 * j + 2 * t) * 41 + 16 * warp + g;
          p[0] = acc[4*j]; p[41] = acc[4*j+1];
          if (warp < 2) { p[8] = acc[4*j+2]; p[49] = acc[4*j+3]; }
        }
      }
    }
  }
  if (mt == 9) {
    __syncthreads();
    float4* red = (float4*)(smem + G_MISC);
    float v[18];
    if (warp < 5) {
      const int row = tid, key = nt * BN + row;
      float n2 = 0.f, r = -INFINITY; int ri = key;
      if (key < SEQ) {
        #pragma unroll
        for (int d = 0; d < 18; d++) { v[d] = bfr(st[row * 41 + d]); n2 += v[d] * v[d]; }
        const bool mufu = (KMASK >> ((key >> 3) & 7)) & 1;
        const float sc = mufu ? 32.f : 0.0625f;
        g_kv[key] = make_uint4(pack2h(v[0] * sc, v[1] * sc), pack2h(v[2] * sc, v[3] * sc), pack2h(v[4] * sc, v[5] * sc), pack2h(v[6] * sc, v[7] * sc));
        g_kv[SEQ + key] = make_uint4(pack2h(v[8] * sc, v[9] * sc), pack2h(v[10] * sc, v[11] * sc), pack2h(v[12] * sc, v[13] * sc), pack2h(v[14] * sc, v[15] * sc));
        g_kv[2 * SEQ + key] = make_uint4(pack2h(v[16] * sc, v[17] * sc), mufu ? 0x3C000000u : 0x00001800u, pack2h(bfr(st[row * 41 + 34]), bfr(st[row * 41 + 35])), 0x00003C00u);
        #pragma unroll
        for (int d = 0; d < 18; d++) g_kraw[d * SEQ + key] = v[d];
        if (!(n2 <= 3e38f)) n2 = 3e38f;
        r = st[row * 41 + 36];
      }
      #pragma unroll
      for (int o = 16; o; o >>= 1) {
        n2 = fmaxf(n2, __shfl_xor_sync(~0u, n2, o));
        float r2 = __shfl_xor_sync(~0u, r, o); int i2 = __shfl_xor_sync(~0u, ri, o);
        if (r2 > r || (r2 == r && i2 < ri)) { r = r2; ri = i2; }
      }
      if (lane == 0) red[warp] = make_float4(n2, 0.f, r, __int_as_float(ri));
    } else if (warp >= 6 && warp < 11) {
      const int row = tid - 192, key = nt * BN + row;
      float vm = 0.f;
      if (key < SEQ) {
        #pragma unroll
        for (int d = 0; d < 18; d++) { v[d] = bfr(st[row * 41 + 18 + d]); float a = fabsf(v[d]); vm = (a <= 3e38f) ? fmaxf(vm, a) : 3e38f; }
        g_kv[3 * SEQ + key] = make_uint4(pack2h(v[0], v[1]), pack2h(v[2], v[3]), pack2h(v[4], v[5]), pack2h(v[6], v[7]));
        g_kv[4 * SEQ + key] = make_uint4(pack2h(v[8], v[9]), pack2h(v[10], v[11]), pack2h(v[12], v[13]), pack2h(v[14], v[15]));
        #pragma unroll
        for (int d = 0; d < 18; d++) g_vraw[d * SEQ + key] = v[d];
        g_gate[key] = __fdividef(1.f, 1.f + __expf(-bfr(st[row * 41 + 37])));
      }
      #pragma unroll
      for (int o = 16; o; o >>= 1) vm = fmaxf(vm, __shfl_xor_sync(~0u, vm, o));
      if (lane == 0) red[warp] = make_float4(0.f, vm, 0.f, 0.f);
    }
    __syncthreads();
    if (tid == 0) {
      float4 a = red[0];
      #pragma unroll
      for (int w = 1; w < 5; w++) { float4 b = red[w]; a.x = fmaxf(a.x, b.x); if (b.z > a.z) { a.z = b.z; a.w = b.w; } }
      a.y = fmaxf(fmaxf(fmaxf(red[6].y, red[7].y), fmaxf(red[8].y, red[9].y)), red[10].y);
      g_stat[nt] = a;
    }
  }
  STAMP0(5);
  __syncwarp();
  cluster_sync();
}

__device__ __forceinline__ float4 load_stat(int lane) {
  uint4 u = ldg16c(&g_stat[min(lane & 15, NTT - 1)]);
  float k2 = __uint_as_float(u.x), vm = __uint_as_float(u.y), r = __uint_as_float(u.z); int ri = (int)u.w;
  #pragma unroll
  for (int o = 8; o; o >>= 1) {
    k2 = fmaxf(k2, __shfl_xor_sync(~0u, k2, o)); vm = fmaxf(vm, __shfl_xor_sync(~0u, vm, o));
    float r2 = __shfl_xor_sync(~0u, r, o); int i2 = __shfl_xor_sync(~0u, ri, o);
    if (r2 > r || (r2 == r && i2 < ri)) { r = r2; ri = i2; }
  }
  return make_float4(k2, vm, r, __int_as_float(ri & (SEQ - 1)));
}

__device__ __forceinline__ float sqrta(float x) { float r; asm("sqrt.approx.f32 %0, %1;" : "=f"(r) : "f"(x)); return r; }
__device__ __forceinline__ uint32_t ex2poly(uint32_t x) {
  uint32_t t = hfma2r(x, 0x02000200u, 0u);
  uint32_t u = hfma2(t, 0xF800F800u, x);
  uint32_t e = hfma2r(u, 0x47AC47ACu, 0x29A029A0u);
  uint32_t p = hfma2(e, u, 0x08000800u);
  return p + (t << 10);
}
__device__ __forceinline__ void softmax64(const uint32_t* s, uint32_t* p) {
  #pragma unroll
  for (int j = 0; j < 8; j++) {
    if ((KMASK >> j) & 1) { p[2*j] = ex2h2(s[2*j]); p[2*j+1] = ex2h2(s[2*j+1]); }
    else { p[2*j] = ex2poly(s[2*j]); p[2*j+1] = ex2poly(s[2*j+1]); }
  }
}
__device__ __forceinline__ void qk64(uint32_t* s, const uint32_t* q, uint32_t sb16, int key0) {
  uint32_t lo = (sb16 | ((PL >> 4) << 16)) + key0;
  wgh_n64_sd0(s, q[0], q[1], q[2], q[3], mk64(lo, 8));
  wgh_n64_sd1(s, q[4], q[5], 0, 0, mk64(lo + (2 * PL >> 4), 8));
}
__device__ __forceinline__ void pv64(float* o, const uint32_t* p, uint32_t sb16, int key0) {
  uint32_t lo = (sb16 | (8 << 16)) + (2 * PL >> 4) + key0;
  #pragma unroll
  for (int j = 0; j < 4; j++) wg_pv(o, p[4*j], p[4*j+1], p[4*j+2], p[4*j+3], mk64(lo + j * 16, PL >> 4));
}
__device__ __forceinline__ void attn_exact(int q0, int h, int lane) {
  #pragma unroll 1
  for (int r = 0; r < 16; r++) {
    float q[18], o[18];
    #pragma unroll
    for (int d = 0; d < 18; d++) { q[d] = __bfloat162float(g_q[(size_t)(q0 + r) * DM + h * 18 + d]) * 0.23570226f; o[d] = 0.f; }
    float m = -INFINITY;
    #pragma unroll 1
    for (int k = lane; k < SEQ; k += 32) {
      float s = 0.f;
      #pragma unroll
      for (int d = 0; d < 18; d++) s = fmaf(q[d], g_kraw[d * SEQ + k], s);
      m = fmaxf(m, s);
    }
    #pragma unroll
    for (int x = 16; x; x >>= 1) m = fmaxf(m, __shfl_xor_sync(~0u, m, x));
    float l = 0.f;
    #pragma unroll 1
    for (int k = lane; k < SEQ; k += 32) {
      float s = 0.f;
      #pragma unroll
      for (int d = 0; d < 18; d++) s = fmaf(q[d], g_kraw[d * SEQ + k], s);
      float p = __expf(s - m);
      l += p;
      #pragma unroll
      for (int d = 0; d < 18; d++) o[d] = fmaf(p, g_vraw[d * SEQ + k], o[d]);
    }
    #pragma unroll
    for (int x = 16; x; x >>= 1) {
      l += __shfl_xor_sync(~0u, l, x);
      #pragma unroll
      for (int d = 0; d < 18; d++) o[d] += __shfl_xor_sync(~0u, o[d], x);
    }
    float inv = __fdividef(1.f, l), mine = 0.f;
    #pragma unroll
    for (int d = 0; d < 18; d++) if (lane == d) mine = o[d];
    if (lane < 18) g_o[(size_t)(q0 + r) * DM + h * 18 + lane] = __float2bfloat16(mine * inv);
  }
}

__device__ __forceinline__ void ffn_slice(int sl, int tid, int barid, float* sx, const __nv_bfloat16* __restrict__ x, const __nv_bfloat16* __restrict__ wgt,
    const __nv_bfloat16* __restrict__ wup, const __nv_bfloat16* __restrict__ wdn) {
  const int ch = tid & 7, rg = tid >> 3;
  const __nv_bfloat16* wp = (ch < 4 ? wgt : wup) + (size_t)rg * FF + sl * 32 + (ch & 3) * 8;
  const __nv_bfloat16* dp = wdn + (size_t)sl * 32 * DM;
  if ((ch & 3) == 0) {
    #pragma unroll 4
    for (int i = 0; i < 36; i++) asm volatile("prefetch.global.L2 [%0];" :: "l"(wp + (size_t)i * 16 * FF));
  }
  #pragma unroll
  for (int i = 0; i < 3; i++) if (tid + i * 128 < 288) asm volatile("prefetch.global.L2 [%0];" :: "l"(dp + (tid + i * 128) * 64));
  pdl_wait();
  const int idx = __float_as_int(load_stat(tid & 31).w);
  for (int i = tid; i < DM; i += 128) sx[i] = __bfloat162float(x[(size_t)idx * DM + i]);
  asm volatile("bar.sync %0, 128;" :: "r"(barid) : "memory");
  float acc[8];
  #pragma unroll
  for (int i = 0; i < 8; i++) acc[i] = 0.f;
  #pragma unroll 1
  for (int i = 0; i < 36; i += 2) {
    uint4 w0 = ldg16(wp + (size_t)i * 16 * FF), w1 = ldg16(wp + (size_t)(i + 1) * 16 * FF);
    float x0 = sx[rg + i * 16], x1 = sx[rg + i * 16 + 16];
    acc[0] = fmaf(x0, bflo(w0.x), acc[0]); acc[1] = fmaf(x0, bfhi(w0.x), acc[1]); acc[2] = fmaf(x0, bflo(w0.y), acc[2]); acc[3] = fmaf(x0, bfhi(w0.y), acc[3]);
    acc[4] = fmaf(x0, bflo(w0.z), acc[4]); acc[5] = fmaf(x0, bfhi(w0.z), acc[5]); acc[6] = fmaf(x0, bflo(w0.w), acc[6]); acc[7] = fmaf(x0, bfhi(w0.w), acc[7]);
    acc[0] = fmaf(x1, bflo(w1.x), acc[0]); acc[1] = fmaf(x1, bfhi(w1.x), acc[1]); acc[2] = fmaf(x1, bflo(w1.y), acc[2]); acc[3] = fmaf(x1, bfhi(w1.y), acc[3]);
    acc[4] = fmaf(x1, bflo(w1.z), acc[4]); acc[5] = fmaf(x1, bfhi(w1.z), acc[5]); acc[6] = fmaf(x1, bflo(w1.w), acc[6]); acc[7] = fmaf(x1, bfhi(w1.w), acc[7]);
  }
  #pragma unroll
  for (int i = 0; i < 8; i++) { acc[i] += __shfl_xor_sync(~0u, acc[i], 8); acc[i] += __shfl_xor_sync(~0u, acc[i], 16); }
  float* sr = sx + DM;
  if ((tid & 31) < 8) {
    #pragma unroll
    for (int i = 0; i < 8; i++) sr[(tid >> 5) * 64 + ch * 8 + i] = acc[i];
  }
  asm volatile("bar.sync %0, 128;" :: "r"(barid) : "memory");
  float* sh = sr + 256;
  if (tid < 32) {
    float gt = bfr(sr[tid] + sr[64 + tid] + sr[128 + tid] + sr[192 + tid]);
    float up = bfr(sr[32 + tid] + sr[96 + tid] + sr[160 + tid] + sr[224 + tid]);
    sh[tid] = bfr(bfr(__fdividef(gt, 1.f + __expf(-gt))) * up);
  }
  asm volatile("bar.sync %0, 128;" :: "r"(barid) : "memory");
  if (tid < 72) {
    #pragma unroll
    for (int i = 0; i < 8; i++) acc[i] = 0.f;
    #pragma unroll 1
    for (int i = 0; i < 32; i += 2) {
      uint4 w0 = ldg16(dp + i * DM + tid * 8), w1 = ldg16(dp + (i + 1) * DM + tid * 8);
      float x0 = sh[i], x1 = sh[i + 1];
      acc[0] = fmaf(x0, bflo(w0.x), acc[0]); acc[1] = fmaf(x0, bfhi(w0.x), acc[1]); acc[2] = fmaf(x0, bflo(w0.y), acc[2]); acc[3] = fmaf(x0, bfhi(w0.y), acc[3]);
      acc[4] = fmaf(x0, bflo(w0.z), acc[4]); acc[5] = fmaf(x0, bfhi(w0.z), acc[5]); acc[6] = fmaf(x0, bflo(w0.w), acc[6]); acc[7] = fmaf(x0, bfhi(w0.w), acc[7]);
      acc[0] = fmaf(x1, bflo(w1.x), acc[0]); acc[1] = fmaf(x1, bfhi(w1.x), acc[1]); acc[2] = fmaf(x1, bflo(w1.y), acc[2]); acc[3] = fmaf(x1, bfhi(w1.y), acc[3]);
      acc[4] = fmaf(x1, bflo(w1.z), acc[4]); acc[5] = fmaf(x1, bfhi(w1.z), acc[5]); acc[6] = fmaf(x1, bflo(w1.w), acc[6]); acc[7] = fmaf(x1, bfhi(w1.w), acc[7]);
    }
    float4* yp = (float4*)(g_ypart + sl * DM + tid * 8);
    yp[0] = make_float4(acc[0], acc[1], acc[2], acc[3]); yp[1] = make_float4(acc[4], acc[5], acc[6], acc[7]);
  }
}

constexpr int K2_SMEM = 5 * PL + 64 + 4096 + 7 * 2048;
__global__ void __launch_bounds__(640, 1) k_attn(const __nv_bfloat16* __restrict__ x, const __nv_bfloat16* __restrict__ wgt, const __nv_bfloat16* __restrict__ wup,
    const __nv_bfloat16* __restrict__ wdn, const __nv_bfloat16* __restrict__ wo) {
  extern __shared__ __align__(1024) uint8_t smem[];
  const uint32_t sbase = (uint32_t)__cvta_generic_to_shared(smem);
  const uint32_t bars = sbase + 5 * PL;
  const int wg = __shfl_sync(0xffffffffu, threadIdx.x >> 7, 0);
  STAMP0(6);
  if (threadIdx.x == 0) {
    #pragma unroll
    for (int i = 0; i < 8; i++) asm volatile("mbarrier.init.shared::cta.b64 [%0], 1;" :: "r"(bars + i * 8) : "memory");
    asm volatile("fence.mbarrier_init.release.cluster;" ::: "memory");
    proxy_fence();
  }
  __syncthreads();
  if (wg == 4) {
    asm volatile("setmaxnreg.dec.sync.aligned.u32 32;");
    const int tid = threadIdx.x - 512;
    if (blockIdx.x < 128) {
      if (tid == 0) {
        pdl_wait();
        #pragma unroll 1
        for (int c = 0; c < 8; c++) {
          asm volatile("mbarrier.arrive.expect_tx.shared::cta.b64 _, [%0], %1;" :: "r"(bars + c * 8), "r"(5 * 4096) : "memory");
          #pragma unroll
          for (int p = 0; p < 5; p++)
            asm volatile("cp.async.bulk.shared::cluster.global.mbarrier::complete_tx::bytes [%0], [%1], %2, [%3];"
              :: "r"(sbase + p * PL + c * 4096), "l"(g_kv + p * SEQ + c * 256), "r"(4096), "r"(bars + c * 8) : "memory");
        }
        pdl_go();
      }
      __syncwarp();
      if (tid < 41 && blockIdx.x * 41 + tid < 5184) asm volatile("prefetch.global.L2 [%0];" :: "l"(wo + (blockIdx.x * 41 + tid) * 64));
      ffn_slice(blockIdx.x, tid, 1, (float*)(smem + 5 * PL + 64), x, wgt, wup, wdn);
      if (tid == 0) STAMP(14);
    }
  } else {
    asm volatile("setmaxnreg.inc.sync.aligned.u32 112;");
    if (blockIdx.x >= 128) {
      ffn_slice(128 + (blockIdx.x - 128) * 4 + wg, threadIdx.x & 127, 2 + wg, (float*)(smem + wg * 4096), x, wgt, wup, wdn);
      STAMP0(15);
    } else {
      const uint32_t sb = sbase >> 4;
      const int warp = (threadIdx.x >> 5) & 3, lane = threadIdx.x & 31, g = lane >> 2, t = lane & 3;
      const int q0 = blockIdx.x * 16;
      pdl_wait();
      STAMP0(7);
      uint32_t qall[2][6];
      uint32_t flags = 0;
      {
        uint32_t raw[2][6];
        #pragma unroll
        for (int i = 0; i < 2; i++) {
          const int h = (wg + i * 4) * 4 + warp;
          const uint32_t* qp0 = (const uint32_t*)(g_q + (size_t)(q0 + g) * DM + h * 18);
          const uint32_t* qp1 = qp0 + 4 * DM;
          raw[i][0] = __ldcg(qp0 + t); raw[i][1] = __ldcg(qp1 + t); raw[i][2] = __ldcg(qp0 + t + 4); raw[i][3] = __ldcg(qp1 + t + 4);
          raw[i][4] = t == 0 ? __ldcg(qp0 + 8) : 0u; raw[i][5] = t == 0 ? __ldcg(qp1 + 8) : 0u;
        }
        const float4 st = load_stat(lane);
        const bool kvbad = !(st.x <= 65536.f) || !(st.y <= 16384.f) || !(st.y >= 0.015625f);
        const float QS = 0.23570226f * 1.44269504f, kn = sqrta(st.x) * (QS * 1.01f * 8.f);
        #pragma unroll
        for (int i = 0; i < 2; i++) {
          float n[2] = {0.f, 0.f};
          #pragma unroll
          for (int j = 0; j < 6; j++) {
            float a = bflo(raw[i][j]), b = bfhi(raw[i][j]);
            n[j & 1] += a * a + b * b;
            qall[i][j] = pack2h(a * (QS / 32.f), b * (QS / 32.f));
          }
          #pragma unroll
          for (int r = 0; r < 2; r++) {
            n[r] += __shfl_xor_sync(~0u, n[r], 1); n[r] += __shfl_xor_sync(~0u, n[r], 2);
            float M = ceilf(sqrta(n[r]) * kn) * 0.125f;
            bool bad = kvbad || !(n[r] <= 65536.f) || !(M <= 40.f);
            if (bad) { flags |= 1u << i; M = 0.f; }
            if (M > 14.f) { flags |= 4u << (2 * i + r); M = 28.f - M; }
            if (t == 1) qall[i][4 + r] = pack2h(M, M - 13.f);
          }
        }
      }
      volatile uint32_t* stash = (volatile uint32_t*)(smem + 5 * PL + 64 + 4096) + threadIdx.x;
      #pragma unroll
      for (int j = 0; j < 6; j++) stash[j * 512] = qall[1][j];
      stash[6 * 512] = flags;
      #pragma unroll
      for (int i = 0; i < 2; i++) {
        const int h = (wg + i * 4) * 4 + warp;
        uint32_t* qa = qall[0];
        if (i == 1) {
          #pragma unroll
          for (int j = 0; j < 6; j++) qa[j] = stash[j * 512];
        }
        float o[12];
        #pragma unroll
        for (int k = 0; k < 12; k++) asm volatile("mov.b32 %0, 0;" : "=f"(o[k]));
        uint32_t s0[16], s1[16], p0[16], p1[16];
        STAMP0(8 + 3 * i);
        if (i == 0) mbar_wait(bars, 0);
        STAMP0(9 + 3 * i);
        wg_fence(); qk64(s0, qa, sb, 0); wg_commit(); wg_wait<0>(); fence_regs<16>(s0);
        #pragma unroll 1
        for (int j = 0; j < 32; j += 2) {
          if (i == 0 && (j & 2)) mbar_wait(bars + (((j + 2) & 31) << 1), 0);
          wg_fence();
          qk64(s1, qa, sb, (j + 1) * 64); wg_commit();
          softmax64(s0, p0);
          wg_fence();
          pv64(o, p0, sb, j * 64); wg_commit();
          wg_wait<1>();
          fence_regs<16>(s1);
          wg_fence();
          qk64(s0, qa, sb, ((j + 2) & 31) * 64); wg_commit();
          softmax64(s1, p1);
          wg_fence();
          pv64(o, p1, sb, (j + 1) * 64); wg_commit();
          wg_wait<1>();
          fence_regs<16>(s0);
        }
        wg_wait<0>();
        fence_regs<12>(o); fence_regs<16>(s0);
        STAMP0(10 + 3 * i);
        flags = stash[6 * 512];
        float l0 = __shfl_sync(0xffffffffu, o[0], lane | 3), l1 = __shfl_sync(0xffffffffu, o[2], lane | 3);
        bool bad = ((flags >> i) & 1) || !(l0 <= 3e38f) || !(l1 <= 3e38f) || !(l0 > 0.f) || !(l1 > 0.f)
                   || (((flags >> (2 + 2 * i)) & 1) && l0 < 256.f) || (((flags >> (3 + 2 * i)) & 1) && l1 < 256.f);
        if (__any_sync(0xffffffffu, bad)) stash[6 * 512] = flags | (64u << i);
        else {
          float r0 = __fdividef(1.f, l0), r1 = __fdividef(1.f, l1);
          uint32_t* op0 = (uint32_t*)(g_o + (size_t)(q0 + g) * DM + h * 18);
          uint32_t* op1 = op0 + 4 * DM;
          op0[t] = pack2(o[4] * r0, o[5] * r0); op1[t] = pack2(o[6] * r1, o[7] * r1);
          op0[t + 4] = pack2(o[8] * r0, o[9] * r0); op1[t + 4] = pack2(o[10] * r1, o[11] * r1);
          if (t == 2) { op0[8] = pack2(o[0] * r0, o[1] * r0); op1[8] = pack2(o[2] * r1, o[3] * r1); }
        }
      }
      flags = stash[6 * 512];
      #pragma unroll 1
      for (int i = 0; i < 2; i++) if ((flags >> (6 + i)) & 1) attn_exact(q0, (wg + i * 4) * 4 + warp, lane);
    }
  }
}
__global__ void __launch_bounds__(256, 1) k_out(const __grid_constant__ CUtensorMap mx, const __grid_constant__ CUtensorMap mwo, const __grid_constant__ CUtensorMap mo,
    const __grid_constant__ CUtensorMap mout) {
  extern __shared__ __align__(1024) uint8_t smem[];
  const int tid = threadIdx.x, lane = tid & 31, g = lane >> 2, t = lane & 3, warp = tid >> 5;
  const int mt = blockIdx.x, nt = blockIdx.y;
  const uint32_t sb = (uint32_t)__cvta_generic_to_shared(smem);
  STAMP0(16);
  gemm_init(sb);
  float* sg = (float*)(smem + G_MISC);
  float* ys = sg + 160;
  if (warp >= 4) {
    if (tid == 128) {
      #pragma unroll 1
      for (int c = 0; c < 9; c++) {
        mbar_expect(sb + G_BAR + c * 8, mt == 9 ? G_SLOT : G_SLOT + 8192);
        if (mt < 9) tma_ld(sb + G_A + c * 8192, &mwo, mt * 64, c * 64, sb + G_BAR + c * 8);
      }
      mbar_expect(sb + G_BAR + 72, G_SLOT);
    }
    pdl_wait();
    if (tid == 128) {
      STAMP(18);
      gemm_load_b(sb, &mo, nt, mt & 1, mt < 9);
      if (mt < 9) {
        mbar_wait(sb + G_BAR + 128 + 16, 0);
        tma_ld(sb + G_B + 2 * G_SLOT, &mx, mt * 64, nt * BN, sb + G_BAR + 72);
        tma_ld(sb + G_B + 2 * G_SLOT + 10240, &mx, mt * 64, nt * BN + 80, sb + G_BAR + 72);
      } else {
        #pragma unroll 1
        for (int c = 0; c < 7; c++) mbar_wait(sb + G_BAR + c * 8, 0);
      }
    } else if (warp >= 5 && mt < 9) {
      const int ht = tid - 160;
      const float4 st = load_stat(lane);
      const int idx = __float_as_int(st.w);
      for (int i = ht; i < BN; i += 96) sg[i] = nt * BN + i < SEQ ? __ldcg(g_gate + nt * BN + i) : 0.f;
      if (idx >= nt * BN && idx < nt * BN + BN) {
        float4 a = make_float4(0.f, 0.f, 0.f, 0.f);
        const float4* yp = (const float4*)(g_ypart + (ht >> 4) * 24 * DM + mt * 64) + (ht & 15);
        #pragma unroll
        for (int i = 0; i < 24; i++) { float4 b = __ldcg(yp + i * (DM / 4)); a.x += b.x; a.y += b.y; a.z += b.z; a.w += b.w; }
        a.x += __shfl_xor_sync(~0u, a.x, 16); a.y += __shfl_xor_sync(~0u, a.y, 16); a.z += __shfl_xor_sync(~0u, a.z, 16); a.w += __shfl_xor_sync(~0u, a.w, 16);
        if (lane < 16) ((float4*)(ys + 64))[(warp - 5) * 16 + lane] = a;
        bar_sync(2, 96);
        const float rs = bfr(__fdividef(1.f, 1.f + __expf(-bfr(st.z))));
        if (ht < 64) ys[ht] = bfr(bfr(ys[64 + ht] + ys[128 + ht] + ys[192 + ht]) * rs);
      }
      if (ht == 0) ((int*)ys)[256] = idx - nt * BN;
      bar_sync(1, 224);
    }
  } else if (mt < 9) {
    float acc[80];
    gemm_main(sb, acc);
    STAMP0(20);
    bar_sync(1, 224);
    mbar_wait(sb + G_BAR + 72, 0);
    const uint32_t ob = sb + G_B + 2 * G_SLOT + ((lane >> 4) * 8 + (lane & 7)) * 128 + (((2 * warp + ((lane >> 3) & 1)) ^ (lane & 7)) << 4);
    const int li = ((int*)ys)[256] - 2 * t;
    #pragma unroll
    for (int j = 0; j < 20; j += 2) {
      uint32_t xr[4], o[4];
      ldsm4t(ob + j * 1024, xr);
      #pragma unroll
      for (int u = 0; u < 4; u++) {
        const int jj = j + (u >> 1);
        const float2 gg = *(const float2*)(sg + 8 * jj + 2 * t);
        float b0 = bflo(xr[u]), b1 = bfhi(xr[u]);
        if ((li >> 1) == 4 * jj) { float y = ys[16 * warp + g + (u & 1) * 8]; if (li & 1) b1 += y; else b0 += y; }
        o[u] = pack2(fmaf(gg.x, acc[4*j + 2*u] - b0, b0), fmaf(gg.y, acc[4*j + 2*u + 1] - b1, b1));
      }
      stsm4t(ob + j * 1024, o[0], o[1], o[2], o[3]);
    }
    proxy_fence();
    bar_sync(3, 128);
    if (tid == 0) {
      tma_st(&mout, sb + G_B + 2 * G_SLOT, mt * 64, nt * BN);
      tma_st(&mout, sb + G_B + 2 * G_SLOT + 10240, mt * 64, nt * BN + 80);
      asm volatile("cp.async.bulk.commit_group;\ncp.async.bulk.wait_group.read 0;" ::: "memory");
    }
    STAMP0(21);
  }
  __syncwarp();
  cluster_sync();
}

typedef CUresult (*EncFn)(CUtensorMap*, CUtensorMapDataType, cuuint32_t, void*, const cuuint64_t*, const cuuint64_t*, const cuuint32_t*, const cuuint32_t*,
                          CUtensorMapInterleave, CUtensorMapSwizzle, CUtensorMapL2promotion, CUtensorMapFloatOOBfill);
static CUtensorMap make_map(EncFn enc, const void* base, int rows, int boxrows) {
  CUtensorMap m;
  cuuint64_t dims[2] = {(cuuint64_t)DM, (cuuint64_t)rows}, strides[1] = {(cuuint64_t)DM * 2};
  cuuint32_t box[2] = {64, (cuuint32_t)boxrows}, es[2] = {1, 1};
  enc(&m, CU_TENSOR_MAP_DATA_TYPE_BFLOAT16, 2, (void*)base, dims, strides, box, es, CU_TENSOR_MAP_INTERLEAVE_NONE, CU_TENSOR_MAP_SWIZZLE_128B,
      CU_TENSOR_MAP_L2_PROMOTION_L2_256B, CU_TENSOR_MAP_FLOAT_OOB_FILL_NONE);
  return m;
}

extern "C" void kernel_launch(void* const* d_in, const int* in_sizes, int n_in, void* d_out, int out_size) {
  typedef const __nv_bfloat16* P;
  P x = (P)d_in[0], wq = (P)d_in[1], wk = (P)d_in[2], wv = (P)d_in[3], wo = (P)d_in[4], wr = (P)d_in[6], wgt = (P)d_in[7], wup = (P)d_in[8], wdn = (P)d_in[9], gw = (P)d_in[10];
  static EncFn enc = nullptr;
  static void *pq = nullptr, *po = nullptr;
  if (!enc) {
    cudaDriverEntryPointQueryResult qr;
    cudaGetDriverEntryPoint("cuTensorMapEncodeTiled", (void**)&enc, cudaEnableDefault, &qr);
    cudaGetSymbolAddress(&pq, g_q); cudaGetSymbolAddress(&po, g_o);
    cudaFuncSetAttribute(k_proj, cudaFuncAttributeMaxDynamicSharedMemorySize, G_SMEM);
    cudaFuncSetAttribute(k_attn, cudaFuncAttributeMaxDynamicSharedMemorySize, K2_SMEM);
    cudaFuncSetAttribute(k_out, cudaFuncAttributeMaxDynamicSharedMemorySize, G_SMEM);
  }
  CUtensorMap mx = make_map(enc, x, SEQ, 80), mwq = make_map(enc, wq, DM, 64), mq = make_map(enc, pq, SEQ, 80), mwo = make_map(enc, wo, DM, 64),
              mo = make_map(enc, po, SEQ, 80), mout = make_map(enc, d_out, SEQ, 80);
  cudaStream_t s = cudaStreamPerThread;
  cudaLaunchAttribute at[2];
  at[0].id = cudaLaunchAttributeClusterDimension; at[0].val.clusterDim.x = 2; at[0].val.clusterDim.y = 1; at[0].val.clusterDim.z = 1;
  at[1].id = cudaLaunchAttributeProgrammaticStreamSerialization; at[1].val.programmaticStreamSerializationAllowed = 1;
  cudaLaunchConfig_t cfg = {};
  cfg.stream = s; cfg.attrs = at; cfg.numAttrs = 1;
  cfg.gridDim = dim3(10, NTT); cfg.blockDim = dim3(384); cfg.dynamicSmemBytes = G_SMEM;
  cudaLaunchKernelEx(&cfg, k_proj, mx, mwq, mq, wk, wv, wr, gw);
  cfg.attrs = at + 1; cfg.numAttrs = 1;
  cfg.gridDim = dim3(132); cfg.blockDim = dim3(640); cfg.dynamicSmemBytes = K2_SMEM;
  cudaLaunchKernelEx(&cfg, k_attn, x, wgt, wup, wdn, wo);
  cfg.attrs = at; cfg.numAttrs = 2;
  cfg.gridDim = dim3(10, NTT); cfg.blockDim = dim3(256); cfg.dynamicSmemBytes = G_SMEM;
  cudaLaunchKernelEx(&cfg, k_out, mx, mwo, mo, mout);
}
```

```cpp
#include <cuda_runtime.h>
#include <cuda_bf16.h>
#include <cuda_fp16.h>
#include <stdint.h>
#include <cuda.h>

constexpr int SEQ = 2048, DM = 576, FF = 4608, NSL = 72, NCTA = 128;
constexpr uint32_t KMASK = 0x25;

__device__ __align__(128) __nv_bfloat16 g_o[SEQ * DM];
__device__ uint4 g_kv[5 * SEQ];
__device__ float g_kraw[SEQ * 18];
__device__ float g_vraw[SEQ * 18];
__device__ float g_gate[SEQ];
__device__ float4 g_stat[NCTA];
__device__ float g_ypart[NSL * DM];
__device__ unsigned g_cnt[40 * 32];

#define STAMP(k)
#define STAMP0(k)
__device__ __forceinline__ void wgh_n64_sd0(uint32_t* d, uint32_t a0, uint32_t a1, uint32_t a2, uint32_t a3, uint64_t bdesc) {
  asm volatile("{\n.reg .pred p;\nsetp.ne.b32 p, 0, 0;\n"
    "wgmma.mma_async.sync.aligned.m64n64k16.f16.f16.f16 {%0, %1, %2, %3, %4, %5, %6, %7, %8, %9, %10, %11, %12, %13, %14, %15}, {%16, %17, %18, %19}, %20, p, 1, 1, 0;\n}\n"
    : "=r"(d[0]), "=r"(d[1]), "=r"(d[2]), "=r"(d[3]), "=r"(d[4]), "=r"(d[5]), "=r"(d[6]), "=r"(d[7]), "=r"(d[8]), "=r"(d[9]), "=r"(d[10]), "=r"(d[11]), "=r"(d[12]), "=r"(d[13]), "=r"(d[14]), "=r"(d[15]) : "r"(a0), "r"(a1), "r"(a2), "r"(a3), "l"(bdesc));
}
__device__ __forceinline__ void wgh_n64_sd1(uint32_t* d, uint32_t a0, uint32_t a1, uint32_t a2, uint32_t a3, uint64_t bdesc) {
  asm volatile("{\n.reg .pred p;\nsetp.ne.b32 p, 1, 0;\n"
    "wgmma.mma_async.sync.aligned.m64n64k16.f16.f16.f16 {%0, %1, %2, %3, %4, %5, %6, %7, %8, %9, %10, %11, %12, %13, %14, %15}, {%16, %17, %18, %19}, %20, p, 1, 1, 0;\n}\n"
    : "+r"(d[0]), "+r"(d[1]), "+r"(d[2]), "+r"(d[3]), "+r"(d[4]), "+r"(d[5]), "+r"(d[6]), "+r"(d[7]), "+r"(d[8]), "+r"(d[9]), "+r"(d[10]), "+r"(d[11]), "+r"(d[12]), "+r"(d[13]), "+r"(d[14]), "+r"(d[15]) : "r"(a0), "r"(a1), "r"(a2), "r"(a3), "l"(bdesc));
}
__device__ __forceinline__ void wg_pv(float* d, uint32_t a0, uint32_t a1, uint32_t a2, uint32_t a3, uint64_t bdesc) {
  asm volatile("{\n.reg .pred p;\nsetp.ne.b32 p, 1, 0;\n"
    "wgmma.mma_async.sync.aligned.m64n24k16.f32.f16.f16 {%0, %1, %2, %3, %4, %5, %6, %7, %8, %9, %10, %11}, {%12, %13, %14, %15}, %16, p, 1, 1, 1;\n}\n"
    : "+f"(d[0]), "+f"(d[1]), "+f"(d[2]), "+f"(d[3]), "+f"(d[4]), "+f"(d[5]), "+f"(d[6]), "+f"(d[7]), "+f"(d[8]), "+f"(d[9]), "+f"(d[10]), "+f"(d[11]) : "r"(a0), "r"(a1), "r"(a2), "r"(a3), "l"(bdesc));
}
__device__ __forceinline__ void wg_ss64(float* d, uint64_t adesc, uint64_t bdesc) {
  asm volatile("{\n.reg .pred p;\nsetp.ne.b32 p, 1, 0;\n"
    "wgmma.mma_async.sync.aligned.m64n64k16.f32.bf16.bf16 {%0, %1, %2, %3, %4, %5, %6, %7, %8, %9, %10, %11, %12, %13, %14, %15, %16, %17, %18, %19, %20, %21, %22, %23, %24, %25, %26, %27, %28, %29, %30, %31}, %32, %33, p, 1, 1, 0, 1;\n}\n"
    : "+f"(d[0]), "+f"(d[1]), "+f"(d[2]), "+f"(d[3]), "+f"(d[4]), "+f"(d[5]), "+f"(d[6]), "+f"(d[7]), "+f"(d[8]), "+f"(d[9]), "+f"(d[10]), "+f"(d[11]), "+f"(d[12]), "+f"(d[13]), "+f"(d[14]), "+f"(d[15]), "+f"(d[16]), "+f"(d[17]), "+f"(d[18]), "+f"(d[19]), "+f"(d[20]), "+f"(d[21]), "+f"(d[22]), "+f"(d[23]), "+f"(d[24]), "+f"(d[25]), "+f"(d[26]), "+f"(d[27]), "+f"(d[28]), "+f"(d[29]), "+f"(d[30]), "+f"(d[31]) : "l"(adesc), "l"(bdesc));
}
__device__ __forceinline__ void wg_ss80(float* d, uint64_t adesc, uint64_t bdesc) {
  asm volatile("{\n.reg .pred p;\nsetp.ne.b32 p, 1, 0;\n"
    "wgmma.mma_async.sync.aligned.m64n80k16.f32.bf16.bf16 {%0, %1, %2, %3, %4, %5, %6, %7, %8, %9, %10, %11, %12, %13, %14, %15, %16, %17, %18, %19, %20, %21, %22, %23, %24, %25, %26, %27, %28, %29, %30, %31, %32, %33, %34, %35, %36, %37, %38, %39}, %40, %41, p, 1, 1, 0, 1;\n}\n"
    : "+f"(d[0]), "+f"(d[1]), "+f"(d[2]), "+f"(d[3]), "+f"(d[4]), "+f"(d[5]), "+f"(d[6]), "+f"(d[7]), "+f"(d[8]), "+f"(d[9]), "+f"(d[10]), "+f"(d[11]), "+f"(d[12]), "+f"(d[13]), "+f"(d[14]), "+f"(d[15]), "+f"(d[16]), "+f"(d[17]), "+f"(d[18]), "+f"(d[19]), "+f"(d[20]), "+f"(d[21]), "+f"(d[22]), "+f"(d[23]), "+f"(d[24]), "+f"(d[25]), "+f"(d[26]), "+f"(d[27]), "+f"(d[28]), "+f"(d[29]), "+f"(d[30]), "+f"(d[31]), "+f"(d[32]), "+f"(d[33]), "+f"(d[34]), "+f"(d[35]), "+f"(d[36]), "+f"(d[37]), "+f"(d[38]), "+f"(d[39]) : "l"(adesc), "l"(bdesc));
}
__device__ __forceinline__ void wg_ss8(float* d, uint64_t adesc, uint64_t bdesc) {
  asm volatile("{\n.reg .pred p;\nsetp.ne.b32 p, 1, 0;\n"
    "wgmma.mma_async.sync.aligned.m64n8k16.f32.bf16.bf16 {%0, %1, %2, %3}, %4, %5, p, 1, 1, 1, 0;\n}\n"
    : "+f"(d[0]), "+f"(d[1]), "+f"(d[2]), "+f"(d[3]) : "l"(adesc), "l"(bdesc));
}

__device__ __forceinline__ void wg_fence() { asm volatile("wgmma.fence.sync.aligned;" ::: "memory"); }
__device__ __forceinline__ void wg_commit() { asm volatile("wgmma.commit_group.sync.aligned;" ::: "memory"); }
template<int N> __device__ __forceinline__ void wg_wait() { asm volatile("wgmma.wait_group.sync.aligned %0;" :: "n"(N) : "memory"); }
__device__ __forceinline__ uint32_t pack2(float lo, float hi) { uint32_t r; asm("cvt.rn.bf16x2.f32 %0, %1, %2;" : "=r"(r) : "f"(hi), "f"(lo)); return r; }
__device__ __forceinline__ uint32_t pack2h(float lo, float hi) { uint32_t r; asm("cvt.rn.f16x2.f32 %0, %1, %2;" : "=r"(r) : "f"(hi), "f"(lo)); return r; }
__device__ __forceinline__ float bflo(uint32_t v) { return __uint_as_float(v << 16); }
__device__ __forceinline__ float bfhi(uint32_t v) { return __uint_as_float(v & 0xffff0000u); }
__device__ __forceinline__ float bfr(float v) { return __bfloat162float(__float2bfloat16(v)); }
__device__ __forceinline__ uint32_t hfma2(uint32_t a, uint32_t b, uint32_t c) { uint32_t r; asm("fma.rn.f16x2 %0, %1, %2, %3;" : "=r"(r) : "r"(a), "r"(b), "r"(c)); return r; }
__device__ __forceinline__ uint32_t hfma2r(uint32_t a, uint32_t b, uint32_t c) { uint32_t r; asm("fma.rn.relu.f16x2 %0, %1, %2, %3;" : "=r"(r) : "r"(a), "r"(b), "r"(c)); return r; }
__device__ __forceinline__ uint32_t ex2h2(uint32_t x) { uint32_t r; asm("ex2.approx.f16x2 %0, %1;" : "=r"(r) : "r"(x)); return r; }
__device__ __forceinline__ uint64_t mk64(uint32_t lo, uint32_t hi) { uint64_t d; asm("mov.b64 %0, {%1, %2};" : "=l"(d) : "r"(lo), "r"(hi)); return d; }
template<int N> __device__ __forceinline__ void fence_regs(float* r) {
  #pragma unroll
  for (int i = 0; i < N; i++) asm volatile("" : "+f"(r[i]) :: "memory");
}
template<int N> __device__ __forceinline__ void fence_regs(uint32_t* r) {
  #pragma unroll
  for (int i = 0; i < N; i++) asm volatile("" : "+r"(r[i]) :: "memory");
}
__device__ __forceinline__ void cp16(uint32_t dst, const void* src) { asm volatile("cp.async.cg.shared.global [%0], [%1], 16;" :: "r"(dst), "l"(src) : "memory"); }
__device__ __forceinline__ void cp4(uint32_t dst, const void* src) { asm volatile("cp.async.ca.shared.global [%0], [%1], 4;" :: "r"(dst), "l"(src) : "memory"); }
__device__ __forceinline__ void cp_commit() { asm volatile("cp.async.commit_group;" ::: "memory"); }
template<int N> __device__ __forceinline__ void cp_wait() { asm volatile("cp.async.wait_group %0;" :: "n"(N) : "memory"); }
__device__ __forceinline__ void proxy_fence() { asm volatile("fence.proxy.async.shared::cta;" ::: "memory"); }
__device__ __forceinline__ void pdl_wait() { asm volatile("griddepcontrol.wait;" ::: "memory"); }
__device__ __forceinline__ void pdl_go() { asm volatile("griddepcontrol.launch_dependents;" ::: "memory"); }
__device__ __forceinline__ uint4 ldg16(const void* p) { uint4 v; asm volatile("ld.global.nc.L1::no_allocate.v4.u32 {%0,%1,%2,%3}, [%4];" : "=r"(v.x), "=r"(v.y), "=r"(v.z), "=r"(v.w) : "l"(p)); return v; }
__device__ __forceinline__ uint4 ldg16c(const void* p) { uint4 v; asm volatile("ld.global.L1::no_allocate.v4.u32 {%0,%1,%2,%3}, [%4];" : "=r"(v.x), "=r"(v.y), "=r"(v.z), "=r"(v.w) : "l"(p) : "memory"); return v; }
__device__ __forceinline__ void mbar_wait(uint32_t bar, uint32_t parity) {
  #pragma unroll 1
  for (int it = 0; it < (1 << 22); it++) {
    uint32_t ok;
    asm volatile("{\n.reg .pred p;\nmbarrier.try_wait.parity.shared::cta.b64 p, [%1], %2;\nselp.u32 %0, 1, 0, p;\n}\n" : "=r"(ok) : "r"(bar), "r"(parity) : "memory");
    if (ok) break;
  }
}
__device__ __forceinline__ void mbar_init(uint32_t bar, uint32_t cnt) { asm volatile("mbarrier.init.shared::cta.b64 [%0], %1;" :: "r"(bar), "r"(cnt) : "memory"); }
__device__ __forceinline__ void mbar_expect(uint32_t bar, uint32_t bytes) { asm volatile("mbarrier.arrive.expect_tx.shared::cta.b64 _, [%0], %1;" :: "r"(bar), "r"(bytes) : "memory"); }
__device__ __forceinline__ void mbar_arrive(uint32_t bar) { asm volatile("mbarrier.arrive.shared::cta.b64 _, [%0];" :: "r"(bar) : "memory"); }
__device__ __forceinline__ void tma2(uint32_t dst, const CUtensorMap* m, int c0, int c1, uint32_t bar) {
  asm volatile("cp.async.bulk.tensor.2d.shared::cluster.global.mbarrier::complete_tx::bytes [%0], [%1, {%3, %4}], [%2];" :: "r"(dst), "l"(m), "r"(bar), "r"(c0), "r"(c1) : "memory");
}
__device__ __forceinline__ void tma3(uint32_t dst, const CUtensorMap* m, int c0, int c1, int c2, uint32_t bar) {
  asm volatile("cp.async.bulk.tensor.3d.shared::cluster.global.mbarrier::complete_tx::bytes [%0], [%1, {%3, %4, %5}], [%2];" :: "r"(dst), "l"(m), "r"(bar), "r"(c0), "r"(c1), "r"(c2) : "memory");
}
__device__ __forceinline__ void bulk(uint32_t dst, const void* src, uint32_t bytes, uint32_t bar) {
  asm volatile("cp.async.bulk.shared::cluster.global.mbarrier::complete_tx::bytes [%0], [%1], %2, [%3];" :: "r"(dst), "l"(src), "r"(bytes), "r"(bar) : "memory");
}
__device__ __forceinline__ void bar_sync(int id, int n) { asm volatile("bar.sync %0, %1;" :: "r"(id), "r"(n) : "memory"); }
__device__ __forceinline__ void bar_arrive(int id, int n) { asm volatile("bar.arrive %0, %1;" :: "r"(id), "r"(n) : "memory"); }
__device__ __forceinline__ void proxy_fence_all() { asm volatile("fence.proxy.async;" ::: "memory"); }
__device__ __forceinline__ void signal(int i) {
  proxy_fence_all();
  asm volatile("fence.acq_rel.gpu;\nred.relaxed.gpu.global.add.u32 [%0], 1;" :: "l"(g_cnt + i * 32) : "memory");
}
__device__ __forceinline__ void await(int i, unsigned n) {
  #pragma unroll 1
  for (int it = 0; it < (1 << 21); it++) {
    unsigned v; asm volatile("ld.acquire.gpu.global.u32 %0, [%1];" : "=r"(v) : "l"(g_cnt + i * 32) : "memory");
    if (v >= n) break;
  }
  proxy_fence_all();
}
__device__ __forceinline__ void ldsm4(uint32_t a, uint32_t* r) {
  asm volatile("ldmatrix.sync.aligned.m8n8.x4.shared.b16 {%0,%1,%2,%3}, [%4];" : "=r"(r[0]), "=r"(r[1]), "=r"(r[2]), "=r"(r[3]) : "r"(a) : "memory");
}
__device__ __forceinline__ void mma16(float* d, const uint32_t* a, uint32_t b0, uint32_t b1) {
  asm volatile("mma.sync.aligned.m16n8k16.row.col.f32.bf16.bf16.f32 {%0,%1,%2,%3}, {%4,%5,%6,%7}, {%8,%9}, {%0,%1,%2,%3};"
    : "+f"(d[0]), "+f"(d[1]), "+f"(d[2]), "+f"(d[3]) : "r"(a[0]), "r"(a[1]), "r"(a[2]), "r"(a[3]), "r"(b0), "r"(b1));
}

constexpr uint32_t KB = 1024, CH = 20480;
constexpr uint32_t S_X = 44 * KB, S_W = 116 * KB;
constexpr uint32_t S_FFN = 160 * KB, S_Q = 192 * KB, S_FLAG = 212 * KB, S_BAR = 224 * KB;
constexpr uint32_t B_X = S_BAR, B_W = B_X + 72, B_E = B_W + 72, B_R = B_E + 40, B_KV = B_R + 8, B_REL = B_KV + 64, B_F = B_REL + 56;
constexpr uint32_t S_ST = S_BAR + 352, S_G = S_BAR + 384, S_Y = S_G + 256, S_H = S_Y + 576, S_XS = S_H + 128, SMEM = S_XS + 1152 + 128;
constexpr int QP = 76;
__device__ __forceinline__ uint32_t wslotA(int c) { return S_W + (c & 3) * 24 * KB; }
__device__ __forceinline__ uint32_t wslotC(int c) { return c == 5 ? S_FFN : (c < 5 ? c : c - 6) * 24 * KB; }
__device__ __forceinline__ uint32_t oslot(int c) { return (c < 5 ? 120 + 8 * c : 152 + 8 * c) * KB; }

template<bool C, int W> __device__ __forceinline__ void gemm(uint32_t sb, uint32_t* sq) {
  constexpr int NA = W ? 40 : 32;
  float acc[NA];
  #pragma unroll
  for (int i = 0; i < NA; i++) asm volatile("mov.b32 %0, 0;" : "=f"(acc[i]));
  const uint32_t hi = 64u | (1u << 30);
  #pragma unroll
  for (int c = 0; c < 9; c++) {
    const uint32_t alo = ((sb + (C ? oslot(c) : S_X + c * 8192)) >> 4) | (1u << 16), blo = ((sb + (C ? wslotC(c) : wslotA(c)) + W * 8192) >> 4) | (512u << 16);
    mbar_wait(sb + B_X + c * 8, C);
    mbar_wait(sb + B_W + c * 8, C);
    wg_fence();
    #pragma unroll
    for (int k = 0; k < 4; k++) { if (W) wg_ss80(acc, mk64(alo + k * 2, hi), mk64(blo + k * 128, hi)); else wg_ss64(acc, mk64(alo + k * 2, hi), mk64(blo + k * 128, hi)); }
    wg_commit();
    if (c >= 1 && c <= (C ? 3 : 5)) { wg_wait<1>(); if ((threadIdx.x & 31) == 0) mbar_arrive(sb + B_E + (c - 1) * 8); }
  }
  wg_wait<0>();
  fence_regs<NA>(acc);
  if (C) bar_sync(7, 256); else bar_sync(3, 416);
  #pragma unroll
  for (int j = 0; j < NA / 4; j++) { sq[W * 32 + j * 4] = pack2(acc[4*j], acc[4*j+1]); sq[8 * QP + W * 32 + j * 4] = pack2(acc[4*j+2], acc[4*j+3]); }
}

__device__ __forceinline__ void special(uint8_t* smem, uint32_t sb, int tok0, int row0) {
  const int tid = threadIdx.x & 127, warp = tid >> 5, lane = tid & 31, g = lane >> 2, t = lane & 3;
  float acc[6][4];
  #pragma unroll
  for (int i = 0; i < 6; i++) { acc[i][0] = acc[i][1] = acc[i][2] = acc[i][3] = 0.f; }
  const uint32_t* raw = (const uint32_t*)smem;
  const int r = row0 + (lane & 15);
  const uint32_t xa = sb + S_X + r * 128 + (((warp * 2 + (lane >> 4)) ^ (r & 7)) << 4);
  const int kb = warp * 16 + 2 * t;
  const uint32_t* pk = raw + kb * 9 + g;
  const uint32_t* pl = g < 2 ? raw + g * 5184 + kb * 9 + 8 : raw + 10368 + (g & 1) * 288 + (kb >> 1);
  const int ls = g < 2 ? 9 : 0, lc = g < 2 ? 576 : 32, l8 = g < 2 ? 72 : 4;
  const uint32_t se = g < 2 ? 0x5410 : 0x3210;
  mbar_wait(sb + B_R, 0);
  #pragma unroll
  for (int c = 0; c < 9; c++) {
    uint32_t a[4];
    mbar_wait(sb + B_X + c * 8, 0);
    ldsm4(xa + c * 8192, a);
    #pragma unroll
    for (int m = 0; m < 2; m++) {
      const uint32_t* p = pk + m * 5184 + c * 576;
      uint32_t w0 = p[0], w1 = p[9], w2 = p[72], w3 = p[81];
      mma16(acc[2*m], a, __byte_perm(w0, w1, 0x5410), __byte_perm(w2, w3, 0x5410));
      mma16(acc[2*m+1], a, __byte_perm(w0, w1, 0x7632), __byte_perm(w2, w3, 0x7632));
    }
    const uint32_t* p = pl + c * lc;
    uint32_t w0 = p[0], w1 = p[ls], w2 = p[l8], w3 = p[l8 + ls];
    mma16(acc[4], a, __byte_perm(w0, w1, se), __byte_perm(w2, w3, se));
    mma16(acc[5], a, __byte_perm(w0, w1, 0x7632), __byte_perm(w2, w3, 0x7632));
  }
  bar_sync(2, 128);
  float* part = (float*)smem;
  #pragma unroll
  for (int h = 0; h < 2; h++) {
    float* q = part + (warp * 16 + g + h * 8) * 44;
    *(float4*)(q + 4 * t) = make_float4(acc[0][2*h], acc[1][2*h], acc[0][2*h+1], acc[1][2*h+1]);
    *(float4*)(q + 16 + 4 * t) = make_float4(acc[2][2*h], acc[3][2*h], acc[2][2*h+1], acc[3][2*h+1]);
    if (t < 2) *(float2*)(q + 32 + 2 * t) = make_float2(acc[4][2*h], acc[4][2*h+1]);
    if (t == 0) *(float2*)(q + 36) = make_float2(acc[5][2*h], acc[5][2*h+1]);
  }
  bar_sync(2, 128);
  #pragma unroll
  for (int i = tid; i < 176; i += 128) {
    float4 a = ((float4*)part)[i], b = ((float4*)part)[i + 176], c = ((float4*)part)[i + 352], d = ((float4*)part)[i + 528];
    ((float4*)part)[i] = make_float4((a.x + b.x) + (c.x + d.x), (a.y + b.y) + (c.y + d.y), (a.z + b.z) + (c.z + d.z), (a.w + b.w) + (c.w + d.w));
  }
  bar_sync(2, 128);
  if (warp == 0) {
    const int isv = lane >> 4, key = tok0 + (lane & 15);
    const float* q = part + (lane & 15) * 44;
    float v[18];
    #pragma unroll
    for (int d = 0; d < 16; d++) v[d] = bfr(q[isv * 16 + d]);
    v[16] = bfr(q[32 + isv]); v[17] = bfr(q[36 + isv]);
    const bool mufu = (KMASK >> ((key >> 3) & 7)) & 1;
    const float sc = isv ? 1.f : mufu ? 32.f : 0.0625f;
    uint4* kv = g_kv + (key >> 8) * 1280 + (key & 255) + isv * 768;
    kv[0] = make_uint4(pack2h(v[0] * sc, v[1] * sc), pack2h(v[2] * sc, v[3] * sc), pack2h(v[4] * sc, v[5] * sc), pack2h(v[6] * sc, v[7] * sc));
    kv[256] = make_uint4(pack2h(v[8] * sc, v[9] * sc), pack2h(v[10] * sc, v[11] * sc), pack2h(v[12] * sc, v[13] * sc), pack2h(v[14] * sc, v[15] * sc));
    ((uint2*)(kv + 512 - isv * 768))[isv] = make_uint2(pack2h(v[16] * sc, v[17] * sc), isv ? 0x00003C00u : mufu ? 0x3C000000u : 0x00001800u);
    float s = 0.f, z = 0.f;
    #pragma unroll
    for (int d = 0; d < 18; d++) { (isv ? g_vraw : g_kraw)[d * SEQ + key] = v[d]; s = isv ? fmaxf(s, fabsf(v[d])) : fmaf(v[d], v[d], s); z = fmaf(v[d], 0.f, z); }
    s += z;
    if (!(s <= 3e38f)) s = 3e38f;
    if (isv) g_gate[key] = __fdividef(1.f, 1.f + __expf(-bfr(q[35])));
    float rr = q[34]; int ri = key;
    #pragma unroll
    for (int o = 8; o; o >>= 1) {
      s = fmaxf(s, __shfl_xor_sync(~0u, s, o));
      float r2 = __shfl_xor_sync(~0u, rr, o); int i2 = __shfl_xor_sync(~0u, ri, o);
      if (r2 > rr || (r2 == rr && i2 < ri)) { rr = r2; ri = i2; }
    }
    const float vm = __shfl_xor_sync(~0u, s, 16);
    if (lane == 0) g_stat[blockIdx.x] = make_float4(s, vm, rr, __int_as_float(ri));
    __syncwarp();
    if (lane == 0) signal(0);
  }
}
__device__ __forceinline__ float sqrta(float x) { float r; asm("sqrt.approx.f32 %0, %1;" : "=f"(r) : "f"(x)); return r; }
__device__ __forceinline__ uint32_t ex2poly(uint32_t x) {
  uint32_t t = hfma2r(x, 0x02000200u, 0u);
  uint32_t u = hfma2(t, 0xF800F800u, x);
  uint32_t e = hfma2r(u, 0x47AC47ACu, 0x29A029A0u);
  uint32_t p = hfma2(e, u, 0x08000800u);
  return p + (t << 10);
}
__device__ __forceinline__ void softmax64(const uint32_t* s, uint32_t* p) {
  #pragma unroll
  for (int j = 0; j < 8; j++) {
    if ((KMASK >> j) & 1) { p[2*j] = ex2h2(s[2*j]); p[2*j+1] = ex2h2(s[2*j+1]); }
    else { p[2*j] = ex2poly(s[2*j]); p[2*j+1] = ex2poly(s[2*j+1]); }
  }
}
__device__ __forceinline__ uint32_t kvt(int j) { return (j >> 2) * (CH >> 4) + (j & 3) * 64; }
__device__ __forceinline__ void qk64(uint32_t* s, const uint32_t* q, uint32_t a16) {
  uint32_t lo = a16 | (256u << 16);
  wgh_n64_sd0(s, q[0], q[1], q[2], q[3], mk64(lo, 8));
  wgh_n64_sd1(s, q[4], q[5], 0, 0, mk64(lo + 512, 8));
}
__device__ __forceinline__ void pv64(float* o, const uint32_t* p, uint32_t a16) {
  uint32_t lo = (a16 | (8u << 16)) + 512;
  #pragma unroll
  for (int j = 0; j < 4; j++) wg_pv(o, p[4*j], p[4*j+1], p[4*j+2], p[4*j+3], mk64(lo + j * 16, 256));
}
__device__ __forceinline__ void attn_exact(const __nv_bfloat16* sq, int q0, int h, int lane) {
  #pragma unroll 1
  for (int r = 0; r < 16; r++) {
    float q[18], o[18];
    #pragma unroll
    for (int d = 0; d < 18; d++) { q[d] = __bfloat162float(sq[r * 2 * QP + d]) * 0.23570226f; o[d] = 0.f; }
    float m = -INFINITY;
    #pragma unroll 1
    for (int k = lane; k < SEQ; k += 32) {
      float s = 0.f;
      #pragma unroll
      for (int d = 0; d < 18; d++) s = fmaf(q[d], __ldcg(g_kraw + d * SEQ + k), s);
      m = fmaxf(m, s);
    }
    #pragma unroll
    for (int x = 16; x; x >>= 1) m = fmaxf(m, __shfl_xor_sync(~0u, m, x));
    float l = 0.f;
    #pragma unroll 1
    for (int k = lane; k < SEQ; k += 32) {
      float s = 0.f;
      #pragma unroll
      for (int d = 0; d < 18; d++) s = fmaf(q[d], __ldcg(g_kraw + d * SEQ + k), s);
      float p = __expf(s - m);
      l += p;
      #pragma unroll
      for (int d = 0; d < 18; d++) o[d] = fmaf(p, __ldcg(g_vraw + d * SEQ + k), o[d]);
    }
    #pragma unroll
    for (int x = 16; x; x >>= 1) {
      l += __shfl_xor_sync(~0u, l, x);
      #pragma unroll
      for (int d = 0; d < 18; d++) o[d] += __shfl_xor_sync(~0u, o[d], x);
    }
    float inv = __fdividef(1.f, l), mine = 0.f;
    #pragma unroll
    for (int d = 0; d < 18; d++) if (lane == d) mine = o[d];
    if (lane < 18) g_o[(size_t)(q0 + r) * DM + h * 18 + lane] = __float2bfloat16(mine * inv);
  }
}

struct Maps { CUtensorMap x, wq, wo, o, wg, wu, wd; };

__device__ __forceinline__ void ffn_load(uint32_t sb, const Maps& mp, int i) {
  const uint32_t bar = sb + B_F + (i & 3) * 8, dst = sb + S_FFN + (i & 3) * 8192;
  mbar_expect(bar, 8192);
  if (i < 18) tma2(dst, i < 9 ? &mp.wg : &mp.wu, blockIdx.x * 64, (i < 9 ? i : i - 9) * 64, bar);
  else tma2(dst, &mp.wd, (i - 18) * 64, blockIdx.x * 64, bar);
}

__global__ void __launch_bounds__(640, 1) k_fused(const __grid_constant__ Maps mp, const __nv_bfloat16* __restrict__ x, const __nv_bfloat16* __restrict__ wk,
    const __nv_bfloat16* __restrict__ wv, const __nv_bfloat16* __restrict__ wr, const __nv_bfloat16* __restrict__ gw, __nv_bfloat16* __restrict__ out) {
  extern __shared__ __align__(1024) uint8_t smem[];
  const uint32_t sb = (uint32_t)__cvta_generic_to_shared(smem);
  const int wg = __shfl_sync(0xffffffffu, threadIdx.x >> 7, 0);
  const int tg = blockIdx.x >> 2, hg = blockIdx.x & 3;
  STAMP0(0);
  if (threadIdx.x == 512) {
    #pragma unroll 1
    for (uint32_t b = B_X; b < B_F + 32; b += 8) mbar_init(sb + b, (b >= B_E && b < B_R) ? 8 : (b >= B_REL && b < B_F) ? 16 : 1);
    asm volatile("fence.mbarrier_init.release.cluster;" ::: "memory");
    proxy_fence();
    mbar_expect(sb + B_R, 43776);
    bulk(sb, wk, 20736, sb + B_R); bulk(sb + 20736, wv, 20736, sb + B_R); bulk(sb + 41472, wr, 1152, sb + B_R); bulk(sb + 42624, gw, 1152, sb + B_R);
    #pragma unroll 1
    for (int c = 0; c < 9; c++) { mbar_expect(sb + B_X + c * 8, 8192); tma2(sb + S_X + c * 8192, &mp.x, c * 64, tg * 64, sb + B_X + c * 8); }
  }
  __syncthreads();
  if (wg == 4) {
    asm volatile("setmaxnreg.dec.sync.aligned.u32 32;");
    const int tid = threadIdx.x - 512, warp = tid >> 5, lane = tid & 31;
    if (tid == 0) {
      #pragma unroll 1
      for (int c = 0; c < 9; c++) {
        if (c >= 4) mbar_wait(sb + B_E + (c - 4) * 8, 0);
        mbar_expect(sb + B_W + c * 8, 24576);
        #pragma unroll
        for (int j = 0; j < 3; j++) tma3(sb + wslotA(c) + j * 8192, &mp.wq, j * 64, hg, c * 64, sb + B_W + c * 8);
      }
    } else if (warp == 1) {
      if (lane == 0) {
        await(0, NCTA);
        STAMP(3);
        #pragma unroll
        for (int c = 0; c < 2; c++) { mbar_expect(sb + B_KV + c * 8, CH); bulk(sb + c * CH, g_kv + c * 1280, CH, sb + B_KV + c * 8); }
      }
      __syncwarp();
      float k2 = 0.f, vm = 0.f, r = -INFINITY; int ri = 0;
      #pragma unroll
      for (int i = 0; i < 4; i++) {
        float4 s = __ldcg(g_stat + i * 32 + lane);
        k2 = fmaxf(k2, s.x); vm = fmaxf(vm, s.y);
        if (s.z > r) { r = s.z; ri = __float_as_int(s.w); }
      }
      const float2 gt = __ldcg((const float2*)(g_gate + tg * 64) + lane);
      bar_sync(3, 416);
      if (lane == 0) {
        #pragma unroll 1
        for (int c = 2; c < 8; c++) { mbar_expect(sb + B_KV + c * 8, CH); bulk(sb + c * CH, g_kv + c * 1280, CH, sb + B_KV + c * 8); }
      }
      #pragma unroll
      for (int o = 16; o; o >>= 1) {
        k2 = fmaxf(k2, __shfl_xor_sync(~0u, k2, o)); vm = fmaxf(vm, __shfl_xor_sync(~0u, vm, o));
        float r2 = __shfl_xor_sync(~0u, r, o); int i2 = __shfl_xor_sync(~0u, ri, o);
        if (r2 > r || (r2 == r && i2 < ri)) { r = r2; ri = i2; }
      }
      if (lane == 0) *(float4*)(smem + S_ST) = make_float4(k2, vm, r, __int_as_float(ri & (SEQ - 1)));
      ((float2*)(smem + S_G))[lane] = gt;
      bar_sync(4, 544);
    }
    bar_sync(1, 128);
    const int idx = *(volatile int*)(smem + S_ST + 12);
    if (blockIdx.x < NSL) {
      if (tid == 0) {
        mbar_wait(sb + B_KV + 56, 0);
        #pragma unroll 1
        for (int i = 0; i < 4; i++) ffn_load(sb, mp, i);
      }
      if (tid < 72) *(uint4*)(smem + S_XS + tid * 16) = ldg16(x + (size_t)idx * DM + tid * 8);
      proxy_fence();
      bar_sync(1, 128);
      float acc[4], gt0 = 0.f, gt1 = 0.f;
      #pragma unroll 1
      for (int i = 0; i < 27; i++) {
        if (i == 0 || i == 9 || i >= 18) {
          #pragma unroll
          for (int k = 0; k < 4; k++) asm volatile("mov.b32 %0, 0;" : "=f"(acc[k]));
        }
        const uint32_t alo = ((sb + S_FFN + (i & 3) * 8192) >> 4) | (64u << 16);
        const uint32_t blo = ((sb + (i < 18 ? S_XS + (i < 9 ? i : i - 9) * 128 : S_H)) >> 4) | (1u << 16);
        mbar_wait(sb + B_F + (i & 3) * 8, (i >> 2) & 1);
        wg_fence();
        #pragma unroll
        for (int k = 0; k < 4; k++) wg_ss8(acc, mk64(alo + k * 128, 64u | (1u << 30)), mk64(blo + k * 2, 8));
        wg_commit(); wg_wait<0>(); fence_regs<4>(acc);
        const int row = warp * 16 + (lane >> 2);
        if (i == 8) { gt0 = bfr(acc[0]); gt1 = bfr(acc[2]); }
        if (i == 17) {
          if ((lane & 3) == 0) {
            __nv_bfloat16* hh = (__nv_bfloat16*)(smem + S_H);
            hh[row] = __float2bfloat16(bfr(__fdividef(gt0, 1.f + __expf(-gt0))) * bfr(acc[0]));
            hh[row + 8] = __float2bfloat16(bfr(__fdividef(gt1, 1.f + __expf(-gt1))) * bfr(acc[2]));
          }
          proxy_fence();
        }
        if (i >= 18 && (lane & 3) == 0) { float* yp = g_ypart + blockIdx.x * DM + (i - 18) * 64 + row; yp[0] = acc[0]; yp[8] = acc[2]; }
        bar_sync(1, 128);
        if (tid == 0 && i < 23) ffn_load(sb, mp, i + 4);
      }
      if (tid == 0) { signal(1); STAMP(14); }
    }
    if ((idx >> 6) == tg) {
      if (tid == 0) await(1, NSL);
      bar_sync(1, 128);
      float4* red = (float4*)(smem + S_FFN + 24 * KB);
      if (tid < 108) {
        const float4* yp = (const float4*)(g_ypart + (tid / 36) * 24 * DM + hg * 144) + tid % 36;
        float4 a = make_float4(0.f, 0.f, 0.f, 0.f);
        #pragma unroll 4
        for (int i = 0; i < 24; i++) { float4 b = __ldcg(yp + i * (DM / 4)); a.x += b.x; a.y += b.y; a.z += b.z; a.w += b.w; }
        red[tid] = a;
      }
      bar_sync(1, 128);
      const float rs = bfr(__fdividef(1.f, 1.f + __expf(-bfr(*(volatile float*)(smem + S_ST + 8)))));
      for (int i = tid; i < 144; i += 128) { const float* f = (const float*)red + i; ((float*)(smem + S_Y))[i] = bfr(bfr(f[0] + f[144] + f[288]) * rs); }
    }
    bar_arrive(5, 640);
    if (tid == 0) {
      #pragma unroll 1
      for (int u = 0; u < 9; u++) {
        const int c = u == 0 ? 5 : u < 6 ? u - 1 : u;
        if (c < 5) mbar_wait(sb + B_REL + (c + 1) * 8, 0);
        if (c > 5) mbar_wait(sb + B_E + (c - 6) * 8, 1);
        mbar_expect(sb + B_W + c * 8, 24576);
        #pragma unroll
        for (int j = 0; j < 3; j++) tma3(sb + wslotC(c) + j * 8192, &mp.wo, j * 64, hg, c * 64, sb + B_W + c * 8);
        if (u == 5) {
          await(8 + tg, 4);
          STAMP(18);
          #pragma unroll 1
          for (int k = 0; k < 9; k++) { mbar_expect(sb + B_X + k * 8, 8192); tma2(sb + oslot(k), &mp.o, k * 64, tg * 64, sb + B_X + k * 8); }
        }
      }
      unsigned old;
      asm volatile("atom.add.acq_rel.gpu.global.u32 %0, [%1], 1;" : "=r"(old) : "l"(g_cnt + 64) : "memory");
      if (old == NCTA - 1) {
        #pragma unroll 1
        for (int i = 0; i < 40; i++) g_cnt[i * 32] = 0;
      }
    }
  } else {
    asm volatile("setmaxnreg.inc.sync.aligned.u32 112;");
    const int warp = (threadIdx.x >> 5) & 3, lane = threadIdx.x & 31, g = lane >> 2, t = lane & 3;
    uint32_t* sq = (uint32_t*)(smem + S_Q) + (warp * 16 + g) * QP;
    if (wg == 0) {
      gemm<false, 0>(sb, sq + t);
      STAMP0(4);
    } else if (wg == 1) {
      gemm<false, 1>(sb, sq + t);
    } else if (wg == 3) {
      special(smem, sb, tg * 64 + hg * 16, hg * 16);
      if (threadIdx.x == 384) STAMP(2);
      bar_arrive(3, 416);
    }
    bar_sync(4, 544);
    STAMP0(7);
    volatile uint32_t* stash = (volatile uint32_t*)(smem + S_FLAG) + threadIdx.x;
    const uint32_t sb16 = sb >> 4;
    const int q0 = tg * 64 + warp * 16;
    #pragma unroll
    for (int i = 0; i < 2; i++) {
      uint32_t qa[6];
      {
        const uint32_t* qp = sq + (i * 4 + wg) * 9;
        uint32_t raw[6] = {qp[t], qp[8 * QP + t], qp[t + 4], qp[8 * QP + t + 4], t == 0 ? qp[8] : 0u, t == 0 ? qp[8 * QP + 8] : 0u};
        const float2 st = *(const float2*)(smem + S_ST);
        const bool kvbad = !(st.x <= 65536.f) || !(st.y <= 16384.f) || !(st.y >= 0.015625f);
        const float QS = 0.23570226f * 1.44269504f, kn = sqrta(st.x) * (QS * 1.01f * 8.f);
        float n[2] = {0.f, 0.f};
        uint32_t flags = i ? (*stash & 8u) : 0u;
        #pragma unroll
        for (int j = 0; j < 6; j++) {
          float a = bflo(raw[j]), b = bfhi(raw[j]);
          n[j & 1] += a * a + b * b;
          qa[j] = pack2h(a * (QS / 32.f), b * (QS / 32.f));
        }
        #pragma unroll
        for (int r = 0; r < 2; r++) {
          n[r] += __shfl_xor_sync(~0u, n[r], 1); n[r] += __shfl_xor_sync(~0u, n[r], 2);
          float M = ceilf(sqrta(n[r]) * kn) * 0.125f;
          bool bad = kvbad || !(n[r] <= 65536.f) || !(M <= 40.f);
          if (bad) { flags |= 1u; M = 0.f; }
          if (M > 14.f) { flags |= 2u << r; M = 28.f - M; }
          if (t == 1) qa[4 + r] = pack2h(M, M - 13.f);
        }
        *stash = flags;
      }
      float o[12];
      #pragma unroll
      for (int k = 0; k < 12; k++) asm volatile("mov.b32 %0, 0;" : "=f"(o[k]));
      uint32_t s0[16], s1[16], p0[16], p1[16];
      if (i == 0) mbar_wait(sb + B_KV, 0);
      STAMP0(9 + 3 * i);
      wg_fence(); qk64(s0, qa, sb16); wg_commit(); wg_wait<0>(); fence_regs<16>(s0);
      #pragma unroll 1
      for (int j = 0; j < 32; j += 2) {
        const uint32_t a0 = sb16 + kvt(j);
        if (i == 0 && (j & 2)) mbar_wait(sb + B_KV + (((j + 2) & 31) << 1), 0);
        wg_fence();
        qk64(s1, qa, a0 + 64); wg_commit();
        softmax64(s0, p0);
        wg_fence();
        pv64(o, p0, a0); wg_commit();
        wg_wait<1>();
        fence_regs<16>(s1);
        if (i == 1 && lane == 0 && (j & 2) == 0 && j) mbar_arrive(sb + B_REL + 2 * j - 8);
        wg_fence();
        qk64(s0, qa, sb16 + kvt((j + 2) & 31)); wg_commit();
        softmax64(s1, p1);
        wg_fence();
        pv64(o, p1, a0 + 64); wg_commit();
        wg_wait<1>();
        fence_regs<16>(s0);
      }
      wg_wait<0>();
      fence_regs<12>(o); fence_regs<16>(s0);
      STAMP0(10 + 3 * i);
      const uint32_t flags = *stash;
      float l0 = __shfl_sync(0xffffffffu, o[0], lane | 3), l1 = __shfl_sync(0xffffffffu, o[2], lane | 3);
      bool bad = (flags & 1) || !(l0 <= 3e38f) || !(l1 <= 3e38f) || !(l0 > 0.f) || !(l1 > 0.f) || ((flags & 2) && l0 < 256.f) || ((flags & 4) && l1 < 256.f);
      if (__any_sync(0xffffffffu, bad)) *stash = flags | (8u << i);
      else {
        float r0 = __fdividef(1.f, l0), r1 = __fdividef(1.f, l1);
        uint32_t* op0 = (uint32_t*)(g_o + (size_t)(q0 + g) * DM + (hg * 8 + i * 4 + wg) * 18);
        uint32_t* op1 = op0 + 4 * DM;
        op0[t] = pack2(o[4] * r0, o[5] * r0); op1[t] = pack2(o[6] * r1, o[7] * r1);
        op0[t + 4] = pack2(o[8] * r0, o[9] * r0); op1[t + 4] = pack2(o[10] * r1, o[11] * r1);
        if (t == 2) { op0[8] = pack2(o[0] * r0, o[1] * r0); op1[8] = pack2(o[2] * r1, o[3] * r1); }
      }
    }
    {
      const uint32_t flags = *stash;
      #pragma unroll 1
      for (int i = 0; i < 2; i++)
        if ((flags >> (3 + i)) & 1) attn_exact((const __nv_bfloat16*)(smem + S_Q) + warp * 32 * QP + (i * 4 + wg) * 18, q0, hg * 8 + i * 4 + wg, lane);
    }
    bar_sync(6, 512);
    if (threadIdx.x == 384) signal(8 + tg);
    uint4 xr[3];
    #pragma unroll
    for (int u = 0; u < 3; u++) {
      const int v = threadIdx.x + u * 512, row = v / 18, c8 = v % 18;
      if (v < 1152) xr[u] = ldg16(x + (size_t)(tg * 64 + row) * DM + hg * 144 + c8 * 8);
    }
    if (wg == 0) gemm<true, 0>(sb, sq + t);
    if (wg == 1) gemm<true, 1>(sb, sq + t);
    STAMP0(20);
    bar_sync(5, 640);
    const int li = *(const int*)(smem + S_ST + 12) - tg * 64;
    #pragma unroll
    for (int u = 0; u < 3; u++) {
      const int v = threadIdx.x + u * 512, row = v / 18, c8 = v % 18;
      if (v < 1152) {
        const float gg = ((const float*)(smem + S_G))[row];
        const uint4 av = *(const uint4*)(smem + S_Q + row * (QP * 4) + c8 * 16);
        const uint32_t aa[4] = {av.x, av.y, av.z, av.w}, xx[4] = {xr[u].x, xr[u].y, xr[u].z, xr[u].w};
        uint32_t r[4];
        #pragma unroll
        for (int k = 0; k < 4; k++) {
          float b0 = bflo(xx[k]), b1 = bfhi(xx[k]);
          if (row == li) { const float* ys = (const float*)(smem + S_Y) + c8 * 8 + 2 * k; b0 += ys[0]; b1 += ys[1]; }
          r[k] = pack2(fmaf(gg, bflo(aa[k]) - b0, b0), fmaf(gg, bfhi(aa[k]) - b1, b1));
        }
        *(uint4*)(out + (size_t)(tg * 64 + row) * DM + hg * 144 + c8 * 8) = make_uint4(r[0], r[1], r[2], r[3]);
      }
    }
    STAMP0(21);
  }
}

typedef CUresult (*EncFn)(CUtensorMap*, CUtensorMapDataType, cuuint32_t, void*, const cuuint64_t*, const cuuint64_t*, const cuuint32_t*, const cuuint32_t*,
                          CUtensorMapInterleave, CUtensorMapSwizzle, CUtensorMapL2promotion, CUtensorMapFloatOOBfill);
static void make_map(EncFn enc, CUtensorMap* m, const void* base, int cols, int rows, bool grouped) {
  cuuint64_t d2[2] = {(cuuint64_t)cols, (cuuint64_t)rows}, s2[1] = {(cuuint64_t)cols * 2}, d3[3] = {144, 4, (cuuint64_t)rows}, s3[2] = {288, (cuuint64_t)cols * 2};
  cuuint32_t b2[2] = {64, 64}, b3[3] = {64, 1, 64}, es[3] = {1, 1, 1};
  enc(m, CU_TENSOR_MAP_DATA_TYPE_BFLOAT16, grouped ? 3 : 2, (void*)base, grouped ? d3 : d2, grouped ? s3 : s2, grouped ? b3 : b2, es, CU_TENSOR_MAP_INTERLEAVE_NONE,
      CU_TENSOR_MAP_SWIZZLE_128B, CU_TENSOR_MAP_L2_PROMOTION_L2_256B, CU_TENSOR_MAP_FLOAT_OOB_FILL_NONE);
}

extern "C" void kernel_launch(void* const* d_in, const int* in_sizes, int n_in, void* d_out, int out_size) {
  typedef const __nv_bfloat16* P;
  static EncFn enc = nullptr;
  static void* po = nullptr;
  if (!enc) {
    cudaDriverEntryPointQueryResult qr;
    cudaGetDriverEntryPoint("cuTensorMapEncodeTiled", (void**)&enc, cudaEnableDefault, &qr);
    cudaGetSymbolAddress(&po, g_o);
    cudaFuncSetAttribute(k_fused, cudaFuncAttributeMaxDynamicSharedMemorySize, SMEM);
  }
  Maps mp;
  make_map(enc, &mp.x, d_in[0], DM, SEQ, false); make_map(enc, &mp.wq, d_in[1], DM, DM, true); make_map(enc, &mp.wo, d_in[4], DM, DM, true);
  make_map(enc, &mp.o, po, DM, SEQ, false); make_map(enc, &mp.wg, d_in[7], FF, DM, false); make_map(enc, &mp.wu, d_in[8], FF, DM, false);
  make_map(enc, &mp.wd, d_in[9], DM, FF, false);
  k_fused<<<NCTA, 640, SMEM, cudaStreamPerThread>>>(mp, (P)d_in[0], (P)d_in[2], (P)d_in[3], (P)d_in[6], (P)d_in[10], (__nv_bfloat16*)d_out);
}
```

```cpp
#include <cuda_runtime.h>
#include <cuda_bf16.h>
#include <cuda_fp16.h>
#include <stdint.h>
#include <cuda.h>

constexpr int SEQ = 2048, DM = 576, FF = 4608, NSL = 72, NCTA = 128;
constexpr uint32_t KMASK = 0x25;

__device__ __align__(128) __nv_bfloat16 g_o[SEQ * DM];
__device__ uint4 g_kv[5 * SEQ];
__device__ float g_kraw[SEQ * 18];
__device__ float g_vraw[SEQ * 18];
__device__ float g_gate[SEQ];
__device__ float4 g_stat[NCTA];
__device__ float g_ypart[NSL * DM];
__device__ unsigned g_cnt[40 * 32];

#define STAMP(k)
#define STAMP0(k)
__device__ __forceinline__ void wgh_n64_sd0(uint32_t* d, uint32_t a0, uint32_t a1, uint32_t a2, uint32_t a3, uint64_t bdesc) {
  asm volatile("{\n.reg .pred p;\nsetp.ne.b32 p, 0, 0;\n"
    "wgmma.mma_async.sync.aligned.m64n64k16.f16.f16.f16 {%0, %1, %2, %3, %4, %5, %6, %7, %8, %9, %10, %11, %12, %13, %14, %15}, {%16, %17, %18, %19}, %20, p, 1, 1, 0;\n}\n"
    : "=r"(d[0]), "=r"(d[1]), "=r"(d[2]), "=r"(d[3]), "=r"(d[4]), "=r"(d[5]), "=r"(d[6]), "=r"(d[7]), "=r"(d[8]), "=r"(d[9]), "=r"(d[10]), "=r"(d[11]), "=r"(d[12]), "=r"(d[13]), "=r"(d[14]), "=r"(d[15]) : "r"(a0), "r"(a1), "r"(a2), "r"(a3), "l"(bdesc));
}
__device__ __forceinline__ void wgh_n64_sd1(uint32_t* d, uint32_t a0, uint32_t a1, uint32_t a2, uint32_t a3, uint64_t bdesc) {
  asm volatile("{\n.reg .pred p;\nsetp.ne.b32 p, 1, 0;\n"
    "wgmma.mma_async.sync.aligned.m64n64k16.f16.f16.f16 {%0, %1, %2, %3, %4, %5, %6, %7, %8, %9, %10, %11, %12, %13, %14, %15}, {%16, %17, %18, %19}, %20, p, 1, 1, 0;\n}\n"
    : "+r"(d[0]), "+r"(d[1]), "+r"(d[2]), "+r"(d[3]), "+r"(d[4]), "+r"(d[5]), "+r"(d[6]), "+r"(d[7]), "+r"(d[8]), "+r"(d[9]), "+r"(d[10]), "+r"(d[11]), "+r"(d[12]), "+r"(d[13]), "+r"(d[14]), "+r"(d[15]) : "r"(a0), "r"(a1), "r"(a2), "r"(a3), "l"(bdesc));
}
__device__ __forceinline__ void wg_pv(float* d, uint32_t a0, uint32_t a1, uint32_t a2, uint32_t a3, uint64_t bdesc) {
  asm volatile("{\n.reg .pred p;\nsetp.ne.b32 p, 1, 0;\n"
    "wgmma.mma_async.sync.aligned.m64n24k16.f32.f16.f16 {%0, %1, %2, %3, %4, %5, %6, %7, %8, %9, %10, %11}, {%12, %13, %14, %15}, %16, p, 1, 1, 1;\n}\n"
    : "+f"(d[0]), "+f"(d[1]), "+f"(d[2]), "+f"(d[3]), "+f"(d[4]), "+f"(d[5]), "+f"(d[6]), "+f"(d[7]), "+f"(d[8]), "+f"(d[9]), "+f"(d[10]), "+f"(d[11]) : "r"(a0), "r"(a1), "r"(a2), "r"(a3), "l"(bdesc));
}
__device__ __forceinline__ void wg_ss64(float* d, uint64_t adesc, uint64_t bdesc) {
  asm volatile("{\n.reg .pred p;\nsetp.ne.b32 p, 1, 0;\n"
    "wgmma.mma_async.sync.aligned.m64n64k16.f32.bf16.bf16 {%0, %1, %2, %3, %4, %5, %6, %7, %8, %9, %10, %11, %12, %13, %14, %15, %16, %17, %18, %19, %20, %21, %22, %23, %24, %25, %26, %27, %28, %29, %30, %31}, %32, %33, p, 1, 1, 0, 1;\n}\n"
    : "+f"(d[0]), "+f"(d[1]), "+f"(d[2]), "+f"(d[3]), "+f"(d[4]), "+f"(d[5]), "+f"(d[6]), "+f"(d[7]), "+f"(d[8]), "+f"(d[9]), "+f"(d[10]), "+f"(d[11]), "+f"(d[12]), "+f"(d[13]), "+f"(d[14]), "+f"(d[15]), "+f"(d[16]), "+f"(d[17]), "+f"(d[18]), "+f"(d[19]), "+f"(d[20]), "+f"(d[21]), "+f"(d[22]), "+f"(d[23]), "+f"(d[24]), "+f"(d[25]), "+f"(d[26]), "+f"(d[27]), "+f"(d[28]), "+f"(d[29]), "+f"(d[30]), "+f"(d[31]) : "l"(adesc), "l"(bdesc));
}
__device__ __forceinline__ void wg_ss80(float* d, uint64_t adesc, uint64_t bdesc) {
  asm volatile("{\n.reg .pred p;\nsetp.ne.b32 p, 1, 0;\n"
    "wgmma.mma_async.sync.aligned.m64n80k16.f32.bf16.bf16 {%0, %1, %2, %3, %4, %5, %6, %7, %8, %9, %10, %11, %12, %13, %14, %15, %16, %17, %18, %19, %20, %21, %22, %23, %24, %25, %26, %27, %28, %29, %30, %31, %32, %33, %34, %35, %36, %37, %38, %39}, %40, %41, p, 1, 1, 0, 1;\n}\n"
    : "+f"(d[0]), "+f"(d[1]), "+f"(d[2]), "+f"(d[3]), "+f"(d[4]), "+f"(d[5]), "+f"(d[6]), "+f"(d[7]), "+f"(d[8]), "+f"(d[9]), "+f"(d[10]), "+f"(d[11]), "+f"(d[12]), "+f"(d[13]), "+f"(d[14]), "+f"(d[15]), "+f"(d[16]), "+f"(d[17]), "+f"(d[18]), "+f"(d[19]), "+f"(d[20]), "+f"(d[21]), "+f"(d[22]), "+f"(d[23]), "+f"(d[24]), "+f"(d[25]), "+f"(d[26]), "+f"(d[27]), "+f"(d[28]), "+f"(d[29]), "+f"(d[30]), "+f"(d[31]), "+f"(d[32]), "+f"(d[33]), "+f"(d[34]), "+f"(d[35]), "+f"(d[36]), "+f"(d[37]), "+f"(d[38]), "+f"(d[39]) : "l"(adesc), "l"(bdesc));
}
__device__ __forceinline__ void wg_ss8(float* d, uint64_t adesc, uint64_t bdesc) {
  asm volatile("{\n.reg .pred p;\nsetp.ne.b32 p, 1, 0;\n"
    "wgmma.mma_async.sync.aligned.m64n8k16.f32.bf16.bf16 {%0, %1, %2, %3}, %4, %5, p, 1, 1, 1, 0;\n}\n"
    : "+f"(d[0]), "+f"(d[1]), "+f"(d[2]), "+f"(d[3]) : "l"(adesc), "l"(bdesc));
}

__device__ __forceinline__ void wg_fence() { asm volatile("wgmma.fence.sync.aligned;" ::: "memory"); }
__device__ __forceinline__ void wg_commit() { asm volatile("wgmma.commit_group.sync.aligned;" ::: "memory"); }
template<int N> __device__ __forceinline__ void wg_wait() { asm volatile("wgmma.wait_group.sync.aligned %0;" :: "n"(N) : "memory"); }
__device__ __forceinline__ uint32_t pack2(float lo, float hi) { uint32_t r; asm("cvt.rn.bf16x2.f32 %0, %1, %2;" : "=r"(r) : "f"(hi), "f"(lo)); return r; }
__device__ __forceinline__ uint32_t pack2h(float lo, float hi) { uint32_t r; asm("cvt.rn.f16x2.f32 %0, %1, %2;" : "=r"(r) : "f"(hi), "f"(lo)); return r; }
__device__ __forceinline__ float bflo(uint32_t v) { return __uint_as_float(v << 16); }
__device__ __forceinline__ float bfhi(uint32_t v) { return __uint_as_float(v & 0xffff0000u); }
__device__ __forceinline__ float bfr(float v) { return __bfloat162float(__float2bfloat16(v)); }
__device__ __forceinline__ uint32_t hfma2(uint32_t a, uint32_t b, uint32_t c) { uint32_t r; asm("fma.rn.f16x2 %0, %1, %2, %3;" : "=r"(r) : "r"(a), "r"(b), "r"(c)); return r; }
__device__ __forceinline__ uint32_t hfma2r(uint32_t a, uint32_t b, uint32_t c) { uint32_t r; asm("fma.rn.relu.f16x2 %0, %1, %2, %3;" : "=r"(r) : "r"(a), "r"(b), "r"(c)); return r; }
__device__ __forceinline__ uint32_t ex2h2(uint32_t x) { uint32_t r; asm("ex2.approx.f16x2 %0, %1;" : "=r"(r) : "r"(x)); return r; }
__device__ __forceinline__ uint64_t mk64(uint32_t lo, uint32_t hi) { uint64_t d; asm("mov.b64 %0, {%1, %2};" : "=l"(d) : "r"(lo), "r"(hi)); return d; }
template<int N> __device__ __forceinline__ void fence_regs(float* r) {
  #pragma unroll
  for (int i = 0; i < N; i++) asm volatile("" : "+f"(r[i]) :: "memory");
}
template<int N> __device__ __forceinline__ void fence_regs(uint32_t* r) {
  #pragma unroll
  for (int i = 0; i < N; i++) asm volatile("" : "+r"(r[i]) :: "memory");
}
__device__ __forceinline__ void cp16(uint32_t dst, const void* src) { asm volatile("cp.async.cg.shared.global [%0], [%1], 16;" :: "r"(dst), "l"(src) : "memory"); }
__device__ __forceinline__ void cp4(uint32_t dst, const void* src) { asm volatile("cp.async.ca.shared.global [%0], [%1], 4;" :: "r"(dst), "l"(src) : "memory"); }
__device__ __forceinline__ void cp_commit() { asm volatile("cp.async.commit_group;" ::: "memory"); }
template<int N> __device__ __forceinline__ void cp_wait() { asm volatile("cp.async.wait_group %0;" :: "n"(N) : "memory"); }
__device__ __forceinline__ void proxy_fence() { asm volatile("fence.proxy.async.shared::cta;" ::: "memory"); }
__device__ __forceinline__ void pdl_wait() { asm volatile("griddepcontrol.wait;" ::: "memory"); }
__device__ __forceinline__ void pdl_go() { asm volatile("griddepcontrol.launch_dependents;" ::: "memory"); }
__device__ __forceinline__ uint4 ldg16(const void* p) { uint4 v; asm volatile("ld.global.nc.L1::no_allocate.v4.u32 {%0,%1,%2,%3}, [%4];" : "=r"(v.x), "=r"(v.y), "=r"(v.z), "=r"(v.w) : "l"(p)); return v; }
__device__ __forceinline__ uint4 ldg16c(const void* p) { uint4 v; asm volatile("ld.global.L1::no_allocate.v4.u32 {%0,%1,%2,%3}, [%4];" : "=r"(v.x), "=r"(v.y), "=r"(v.z), "=r"(v.w) : "l"(p) : "memory"); return v; }
__device__ __forceinline__ void mbar_wait(uint32_t bar, uint32_t parity) {
  #pragma unroll 1
  for (int it = 0; it < (1 << 22); it++) {
    uint32_t ok;
    asm volatile("{\n.reg .pred p;\nmbarrier.try_wait.parity.shared::cta.b64 p, [%1], %2;\nselp.u32 %0, 1, 0, p;\n}\n" : "=r"(ok) : "r"(bar), "r"(parity) : "memory");
    if (ok) break;
  }
}
__device__ __forceinline__ void mbar_init(uint32_t bar, uint32_t cnt) { asm volatile("mbarrier.init.shared::cta.b64 [%0], %1;" :: "r"(bar), "r"(cnt) : "memory"); }
__device__ __forceinline__ void mbar_expect(uint32_t bar, uint32_t bytes) { asm volatile("mbarrier.arrive.expect_tx.shared::cta.b64 _, [%0], %1;" :: "r"(bar), "r"(bytes) : "memory"); }
__device__ __forceinline__ void mbar_arrive(uint32_t bar) { asm volatile("mbarrier.arrive.shared::cta.b64 _, [%0];" :: "r"(bar) : "memory"); }
__device__ __forceinline__ void tma2(uint32_t dst, const CUtensorMap* m, int c0, int c1, uint32_t bar) {
  asm volatile("cp.async.bulk.tensor.2d.shared::cluster.global.mbarrier::complete_tx::bytes [%0], [%1, {%3, %4}], [%2];" :: "r"(dst), "l"(m), "r"(bar), "r"(c0), "r"(c1) : "memory");
}
__device__ __forceinline__ void tma3(uint32_t dst, const CUtensorMap* m, int c0, int c1, int c2, uint32_t bar) {
  asm volatile("cp.async.bulk.tensor.3d.shared::cluster.global.mbarrier::complete_tx::bytes [%0], [%1, {%3, %4, %5}], [%2];" :: "r"(dst), "l"(m), "r"(bar), "r"(c0), "r"(c1), "r"(c2) : "memory");
}
__device__ __forceinline__ void bulk(uint32_t dst, const void* src, uint32_t bytes, uint32_t bar) {
  asm volatile("cp.async.bulk.shared::cluster.global.mbarrier::complete_tx::bytes [%0], [%1], %2, [%3];" :: "r"(dst), "l"(src), "r"(bytes), "r"(bar) : "memory");
}
__device__ __forceinline__ void bar_sync(int id, int n) { asm volatile("bar.sync %0, %1;" :: "r"(id), "r"(n) : "memory"); }
__device__ __forceinline__ void bar_arrive(int id, int n) { asm volatile("bar.arrive %0, %1;" :: "r"(id), "r"(n) : "memory"); }
__device__ __forceinline__ void proxy_fence_all() { asm volatile("fence.proxy.async;" ::: "memory"); }
__device__ __forceinline__ void signal(int i) {
  proxy_fence_all();
  asm volatile("fence.acq_rel.gpu;\nred.relaxed.gpu.global.add.u32 [%0], 1;" :: "l"(g_cnt + i * 32) : "memory");
}
__device__ __forceinline__ void await(int i, unsigned n) {
  #pragma unroll 1
  for (int it = 0; it < (1 << 21); it++) {
    unsigned v; asm volatile("ld.acquire.gpu.global.u32 %0, [%1];" : "=r"(v) : "l"(g_cnt + i * 32) : "memory");
    if (v >= n) break;
  }
  proxy_fence_all();
}
__device__ __forceinline__ void ldsm4(uint32_t a, uint32_t* r) {
  asm volatile("ldmatrix.sync.aligned.m8n8.x4.shared.b16 {%0,%1,%2,%3}, [%4];" : "=r"(r[0]), "=r"(r[1]), "=r"(r[2]), "=r"(r[3]) : "r"(a) : "memory");
}
__device__ __forceinline__ void mma16(float* d, const uint32_t* a, uint32_t b0, uint32_t b1) {
  asm volatile("mma.sync.aligned.m16n8k16.row.col.f32.bf16.bf16.f32 {%0,%1,%2,%3}, {%4,%5,%6,%7}, {%8,%9}, {%0,%1,%2,%3};"
    : "+f"(d[0]), "+f"(d[1]), "+f"(d[2]), "+f"(d[3]) : "r"(a[0]), "r"(a[1]), "r"(a[2]), "r"(a[3]), "r"(b0), "r"(b1));
}

constexpr uint32_t KB = 1024, CH = 20480;
constexpr uint32_t S_X = 44 * KB, S_W = 116 * KB;
constexpr uint32_t S_FFN = 160 * KB, S_Q = 192 * KB, S_FLAG = 212 * KB, S_BAR = 224 * KB;
constexpr uint32_t B_X = S_BAR, B_W = B_X + 72, B_E = B_W + 72, B_R = B_E + 40, B_KV = B_R + 8, B_REL = B_KV + 64, B_F = B_REL + 56;
constexpr uint32_t S_ST = S_BAR + 352, S_G = S_BAR + 384, S_Y = S_G + 256, S_H = S_Y + 576, S_XS = S_H + 128, SMEM = S_XS + 1152 + 128;
constexpr int QP = 76;
__device__ __forceinline__ uint32_t wslotA(int c) { return S_W + (c & 3) * 24 * KB; }
__device__ __forceinline__ uint32_t wslotC(int c) { return c == 5 ? S_FFN : (c < 5 ? c : c - 6) * 24 * KB; }
__device__ __forceinline__ uint32_t oslot(int c) { return (c < 5 ? 120 + 8 * c : 152 + 8 * c) * KB; }

template<bool C, int W> __device__ __forceinline__ void gemm(uint32_t sb, uint32_t* sq) {
  constexpr int NA = W ? 40 : 32;
  float acc[NA];
  #pragma unroll
  for (int i = 0; i < NA; i++) asm volatile("mov.b32 %0, 0;" : "=f"(acc[i]));
  const uint32_t hi = 64u | (1u << 30);
  #pragma unroll
  for (int c = 0; c < 9; c++) {
    const uint32_t alo = ((sb + (C ? oslot(c) : S_X + c * 8192)) >> 4) | (1u << 16), blo = ((sb + (C ? wslotC(c) : wslotA(c)) + W * 8192) >> 4) | (512u << 16);
    mbar_wait(sb + B_X + c * 8, C);
    mbar_wait(sb + B_W + c * 8, C);
    wg_fence();
    #pragma unroll
    for (int k = 0; k < 4; k++) { if (W) wg_ss80(acc, mk64(alo + k * 2, hi), mk64(blo + k * 128, hi)); else wg_ss64(acc, mk64(alo + k * 2, hi), mk64(blo + k * 128, hi)); }
    wg_commit();
    if (c >= 1 && c <= (C ? 3 : 5)) { wg_wait<1>(); if ((threadIdx.x & 31) == 0) mbar_arrive(sb + B_E + (c - 1) * 8); }
  }
  wg_wait<0>();
  fence_regs<NA>(acc);
  if (C) bar_sync(7, 256); else bar_sync(3, 416);
  #pragma unroll
  for (int j = 0; j < NA / 4; j++) { sq[W * 32 + j * 4] = pack2(acc[4*j], acc[4*j+1]); sq[8 * QP + W * 32 + j * 4] = pack2(acc[4*j+2], acc[4*j+3]); }
}

__device__ __forceinline__ void special(uint8_t* smem, uint32_t sb, int tok0, int row0) {
  const int tid = threadIdx.x & 127, warp = tid >> 5, lane = tid & 31, g = lane >> 2, t = lane & 3;
  float acc[6][4];
  #pragma unroll
  for (int i = 0; i < 6; i++) { acc[i][0] = acc[i][1] = acc[i][2] = acc[i][3] = 0.f; }
  const uint32_t* raw = (const uint32_t*)smem;
  const int r = row0 + (lane & 15);
  const uint32_t xa = sb + S_X + r * 128 + (((warp * 2 + (lane >> 4)) ^ (r & 7)) << 4);
  const int kb = warp * 16 + 2 * t;
  const uint32_t* pk = raw + kb * 9 + g;
  const uint32_t* pl = g < 2 ? raw + g * 5184 + kb * 9 + 8 : raw + 10368 + (g & 1) * 288 + (kb >> 1);
  const int ls = g < 2 ? 9 : 0, lc = g < 2 ? 576 : 32, l8 = g < 2 ? 72 : 4;
  const uint32_t se = g < 2 ? 0x5410 : 0x3210;
  mbar_wait(sb + B_R, 0);
  #pragma unroll
  for (int c = 0; c < 9; c++) {
    uint32_t a[4];
    mbar_wait(sb + B_X + c * 8, 0);
    ldsm4(xa + c * 8192, a);
    #pragma unroll
    for (int m = 0; m < 2; m++) {
      const uint32_t* p = pk + m * 5184 + c * 576;
      uint32_t w0 = p[0], w1 = p[9], w2 = p[72], w3 = p[81];
      mma16(acc[2*m], a, __byte_perm(w0, w1, 0x5410), __byte_perm(w2, w3, 0x5410));
      mma16(acc[2*m+1], a, __byte_perm(w0, w1, 0x7632), __byte_perm(w2, w3, 0x7632));
    }
    const uint32_t* p = pl + c * lc;
    uint32_t w0 = p[0], w1 = p[ls], w2 = p[l8], w3 = p[l8 + ls];
    mma16(acc[4], a, __byte_perm(w0, w1, se), __byte_perm(w2, w3, se));
    mma16(acc[5], a, __byte_perm(w0, w1, 0x7632), __byte_perm(w2, w3, 0x7632));
  }
  bar_sync(2, 128);
  float* part = (float*)smem;
  #pragma unroll
  for (int h = 0; h < 2; h++) {
    float* q = part + (warp * 16 + g + h * 8) * 44;
    *(float4*)(q + 4 * t) = make_float4(acc[0][2*h], acc[1][2*h], acc[0][2*h+1], acc[1][2*h+1]);
    *(float4*)(q + 16 + 4 * t) = make_float4(acc[2][2*h], acc[3][2*h], acc[2][2*h+1], acc[3][2*h+1]);
    if (t < 2) *(float2*)(q + 32 + 2 * t) = make_float2(acc[4][2*h], acc[4][2*h+1]);
    if (t == 0) *(float2*)(q + 36) = make_float2(acc[5][2*h], acc[5][2*h+1]);
  }
  bar_sync(2, 128);
  #pragma unroll
  for (int i = tid; i < 176; i += 128) {
    float4 a = ((float4*)part)[i], b = ((float4*)part)[i + 176], c = ((float4*)part)[i + 352], d = ((float4*)part)[i + 528];
    ((float4*)part)[i] = make_float4((a.x + b.x) + (c.x + d.x), (a.y + b.y) + (c.y + d.y), (a.z + b.z) + (c.z + d.z), (a.w + b.w) + (c.w + d.w));
  }
  bar_sync(2, 128);
  if (warp == 0) {
    const int isv = lane >> 4, key = tok0 + (lane & 15);
    const float* q = part + (lane & 15) * 44;
    float v[18];
    #pragma unroll
    for (int d = 0; d < 16; d++) v[d] = bfr(q[isv * 16 + d]);
    v[16] = bfr(q[32 + isv]); v[17] = bfr(q[36 + isv]);
    const bool mufu = (KMASK >> ((key >> 3) & 7)) & 1;
    const float sc = isv ? 1.f : mufu ? 32.f : 0.0625f;
    uint4* kv = g_kv + (key >> 8) * 1280 + (key & 255) + isv * 768;
    kv[0] = make_uint4(pack2h(v[0] * sc, v[1] * sc), pack2h(v[2] * sc, v[3] * sc), pack2h(v[4] * sc, v[5] * sc), pack2h(v[6] * sc, v[7] * sc));
    kv[256] = make_uint4(pack2h(v[8] * sc, v[9] * sc), pack2h(v[10] * sc, v[11] * sc), pack2h(v[12] * sc, v[13] * sc), pack2h(v[14] * sc, v[15] * sc));
    ((uint2*)(kv + 512 - isv * 768))[isv] = make_uint2(pack2h(v[16] * sc, v[17] * sc), isv ? 0x00003C00u : mufu ? 0x3C000000u : 0x00001800u);
    float s = 0.f, z = 0.f;
    #pragma unroll
    for (int d = 0; d < 18; d++) { (isv ? g_vraw : g_kraw)[d * SEQ + key] = v[d]; s = isv ? fmaxf(s, fabsf(v[d])) : fmaf(v[d], v[d], s); z = fmaf(v[d], 0.f, z); }
    s += z;
    if (!(s <= 3e38f)) s = 3e38f;
    if (isv) g_gate[key] = __fdividef(1.f, 1.f + __expf(-bfr(q[35])));
    float rr = q[34]; int ri = key;
    #pragma unroll
    for (int o = 8; o; o >>= 1) {
      s = fmaxf(s, __shfl_xor_sync(~0u, s, o));
      float r2 = __shfl_xor_sync(~0u, rr, o); int i2 = __shfl_xor_sync(~0u, ri, o);
      if (r2 > rr || (r2 == rr && i2 < ri)) { rr = r2; ri = i2; }
    }
    const float vm = __shfl_xor_sync(~0u, s, 16);
    if (lane == 0) g_stat[blockIdx.x] = make_float4(s, vm, rr, __int_as_float(ri));
    __syncwarp();
    if (lane == 0) signal(0);
  }
}
__device__ __forceinline__ bool elect() { uint32_t p; asm volatile("{\n.reg .pred q;\nelect.sync _|q, 0xffffffff;\nselp.u32 %0, 1, 0, q;\n}" : "=r"(p)); return p; }
__device__ __forceinline__ float sqrta(float x) { float r; asm("sqrt.approx.f32 %0, %1;" : "=f"(r) : "f"(x)); return r; }
__device__ __forceinline__ uint32_t ex2poly(uint32_t x) {
  uint32_t t = hfma2r(x, 0x02000200u, 0u);
  uint32_t u = hfma2(t, 0xF800F800u, x);
  uint32_t e = hfma2r(u, 0x47AC47ACu, 0x29A029A0u);
  uint32_t p = hfma2(e, u, 0x08000800u);
  return p + __funnelshift_l(t, t, 10);
}
__device__ __forceinline__ void softmax64(const uint32_t* s, uint32_t* p) {
  #pragma unroll
  for (int j = 0; j < 8; j++) {
    if ((KMASK >> j) & 1) { p[2*j] = ex2h2(s[2*j]); p[2*j+1] = ex2h2(s[2*j+1]); }
    else { p[2*j] = ex2poly(s[2*j]); p[2*j+1] = ex2poly(s[2*j+1]); }
  }
}
__device__ __forceinline__ uint32_t kvt(int j) { return (j >> 2) * (CH >> 4) + (j & 3) * 64; }
__device__ __forceinline__ void qk64(uint32_t* s, const uint32_t* q, uint32_t a16) {
  uint32_t lo = a16 | (256u << 16);
  wgh_n64_sd0(s, q[0], q[1], q[2], q[3], mk64(lo, 8));
  wgh_n64_sd1(s, q[4], q[5], q[6], q[7], mk64(lo + 512, 8));
}
__device__ __forceinline__ void pv64(float* o, const uint32_t* p, uint32_t a16) {
  uint32_t lo = (a16 | (8u << 16)) + 512;
  #pragma unroll
  for (int j = 0; j < 4; j++) wg_pv(o, p[4*j], p[4*j+1], p[4*j+2], p[4*j+3], mk64(lo + j * 16, 256));
}
__device__ __forceinline__ void attn_exact(const __nv_bfloat16* sq, int q0, int h, int lane) {
  #pragma unroll 1
  for (int r = 0; r < 16; r++) {
    float q[18], o[18];
    #pragma unroll
    for (int d = 0; d < 18; d++) { q[d] = __bfloat162float(sq[r * 2 * QP + d]) * 0.23570226f; o[d] = 0.f; }
    float m = -INFINITY;
    #pragma unroll 1
    for (int k = lane; k < SEQ; k += 32) {
      float s = 0.f;
      #pragma unroll
      for (int d = 0; d < 18; d++) s = fmaf(q[d], __ldcg(g_kraw + d * SEQ + k), s);
      m = fmaxf(m, s);
    }
    #pragma unroll
    for (int x = 16; x; x >>= 1) m = fmaxf(m, __shfl_xor_sync(~0u, m, x));
    float l = 0.f;
    #pragma unroll 1
    for (int k = lane; k < SEQ; k += 32) {
      float s = 0.f;
      #pragma unroll
      for (int d = 0; d < 18; d++) s = fmaf(q[d], __ldcg(g_kraw + d * SEQ + k), s);
      float p = __expf(s - m);
      l += p;
      #pragma unroll
      for (int d = 0; d < 18; d++) o[d] = fmaf(p, __ldcg(g_vraw + d * SEQ + k), o[d]);
    }
    #pragma unroll
    for (int x = 16; x; x >>= 1) {
      l += __shfl_xor_sync(~0u, l, x);
      #pragma unroll
      for (int d = 0; d < 18; d++) o[d] += __shfl_xor_sync(~0u, o[d], x);
    }
    float inv = __fdividef(1.f, l), mine = 0.f;
    #pragma unroll
    for (int d = 0; d < 18; d++) if (lane == d) mine = o[d];
    if (lane < 18) g_o[(size_t)(q0 + r) * DM + h * 18 + lane] = __float2bfloat16(mine * inv);
  }
}

struct Maps { CUtensorMap x, wq, wo, o, wg, wu, wd; };

__device__ __forceinline__ void ffn_load(uint32_t sb, const Maps& mp, int i) {
  const uint32_t bar = sb + B_F + (i & 3) * 8, dst = sb + S_FFN + (i & 3) * 8192;
  mbar_expect(bar, 8192);
  if (i < 18) tma2(dst, i < 9 ? &mp.wg : &mp.wu, blockIdx.x * 64, (i < 9 ? i : i - 9) * 64, bar);
  else tma2(dst, &mp.wd, (i - 18) * 64, blockIdx.x * 64, bar);
}

#define RETID uint32_t tx_; asm volatile("mov.u32 %0, %%tid.x;" : "=r"(tx_)); const int warp = (tx_ >> 5) & 3, lane = tx_ & 31, g = lane >> 2, t = lane & 3, wg = tx_ >> 7, q0 = tg * 64 + warp * 16; \
  volatile uint32_t* stash = (volatile uint32_t*)(smem + S_FLAG) + tx_; volatile uint8_t* fl = smem + S_FLAG - 512 + tx_; (void)g; (void)t; (void)q0; (void)stash; (void)fl; (void)wg;
#define PVC wg_commit();
#define WN 2
__global__ void __launch_bounds__(640, 1) k_fused(const __grid_constant__ Maps mp, const __nv_bfloat16* __restrict__ x, const __nv_bfloat16* __restrict__ wk,
    const __nv_bfloat16* __restrict__ wv, const __nv_bfloat16* __restrict__ wr, const __nv_bfloat16* __restrict__ gw, __nv_bfloat16* __restrict__ out) {
  extern __shared__ __align__(1024) uint8_t smem[];
  const uint32_t sb = (uint32_t)__cvta_generic_to_shared(smem);
  const int wg = __shfl_sync(0xffffffffu, threadIdx.x >> 7, 0);
  const int tg = blockIdx.x >> 2, hg = blockIdx.x & 3;
  STAMP0(0);
  if (threadIdx.x == 512) {
    #pragma unroll 1
    for (uint32_t b = B_X; b < B_F + 32; b += 8) mbar_init(sb + b, (b >= B_E && b < B_R) ? 8 : (b >= B_REL && b < B_F) ? 16 : 1);
    asm volatile("fence.mbarrier_init.release.cluster;" ::: "memory");
    proxy_fence();
    mbar_expect(sb + B_R, 43776);
    bulk(sb, wk, 20736, sb + B_R); bulk(sb + 20736, wv, 20736, sb + B_R); bulk(sb + 41472, wr, 1152, sb + B_R); bulk(sb + 42624, gw, 1152, sb + B_R);
    #pragma unroll 1
    for (int c = 0; c < 9; c++) { mbar_expect(sb + B_X + c * 8, 8192); tma2(sb + S_X + c * 8192, &mp.x, c * 64, tg * 64, sb + B_X + c * 8); }
  }
  __syncthreads();
  if (wg == 4) {
    asm volatile("setmaxnreg.dec.sync.aligned.u32 32;");
    const int tid = threadIdx.x - 512, warp = tid >> 5, lane = tid & 31;
    if (tid == 0) {
      #pragma unroll 1
      for (int c = 0; c < 9; c++) {
        if (c >= 4) mbar_wait(sb + B_E + (c - 4) * 8, 0);
        mbar_expect(sb + B_W + c * 8, 24576);
        #pragma unroll
        for (int j = 0; j < 3; j++) tma3(sb + wslotA(c) + j * 8192, &mp.wq, j * 64, hg, c * 64, sb + B_W + c * 8);
      }
    } else if (warp == 1) {
      if (lane == 0) {
        await(0, NCTA);
        STAMP(3);
        #pragma unroll
        for (int c = 0; c < 2; c++) { mbar_expect(sb + B_KV + c * 8, CH); bulk(sb + c * CH, g_kv + c * 1280, CH, sb + B_KV + c * 8); }
      }
      __syncwarp();
      float k2 = 0.f, vm = 0.f, r = -INFINITY; int ri = 0;
      #pragma unroll
      for (int i = 0; i < 4; i++) {
        float4 s = __ldcg(g_stat + i * 32 + lane);
        k2 = fmaxf(k2, s.x); vm = fmaxf(vm, s.y);
        if (s.z > r) { r = s.z; ri = __float_as_int(s.w); }
      }
      const float2 gt = __ldcg((const float2*)(g_gate + tg * 64) + lane);
      bar_sync(3, 416);
      if (lane == 0) {
        #pragma unroll 1
        for (int c = 2; c < 8; c++) { mbar_expect(sb + B_KV + c * 8, CH); bulk(sb + c * CH, g_kv + c * 1280, CH, sb + B_KV + c * 8); }
      }
      #pragma unroll
      for (int o = 16; o; o >>= 1) {
        k2 = fmaxf(k2, __shfl_xor_sync(~0u, k2, o)); vm = fmaxf(vm, __shfl_xor_sync(~0u, vm, o));
        float r2 = __shfl_xor_sync(~0u, r, o); int i2 = __shfl_xor_sync(~0u, ri, o);
        if (r2 > r || (r2 == r && i2 < ri)) { r = r2; ri = i2; }
      }
      if (lane == 0) *(float4*)(smem + S_ST) = make_float4(k2, vm, r, __int_as_float(ri & (SEQ - 1)));
      ((float2*)(smem + S_G))[lane] = gt;
      bar_sync(4, 544);
    }
    bar_sync(1, 128);
    const int idx = *(volatile int*)(smem + S_ST + 12);
    if (blockIdx.x < NSL) {
      if (tid == 0) {
        mbar_wait(sb + B_KV + 56, 0);
        #pragma unroll 1
        for (int i = 0; i < 4; i++) ffn_load(sb, mp, i);
      }
      if (tid < 72) *(uint4*)(smem + S_XS + tid * 16) = ldg16(x + (size_t)idx * DM + tid * 8);
      proxy_fence();
      bar_sync(1, 128);
      float acc[4], gt0 = 0.f, gt1 = 0.f;
      #pragma unroll 1
      for (int i = 0; i < 27; i++) {
        if (i == 0 || i == 9 || i >= 18) {
          #pragma unroll
          for (int k = 0; k < 4; k++) asm volatile("mov.b32 %0, 0;" : "=f"(acc[k]));
        }
        const uint32_t alo = ((sb + S_FFN + (i & 3) * 8192) >> 4) | (64u << 16);
        const uint32_t blo = ((sb + (i < 18 ? S_XS + (i < 9 ? i : i - 9) * 128 : S_H)) >> 4) | (1u << 16);
        mbar_wait(sb + B_F + (i & 3) * 8, (i >> 2) & 1);
        wg_fence();
        #pragma unroll
        for (int k = 0; k < 4; k++) wg_ss8(acc, mk64(alo + k * 128, 64u | (1u << 30)), mk64(blo + k * 2, 8));
        wg_commit(); wg_wait<0>(); fence_regs<4>(acc);
        const int row = warp * 16 + (lane >> 2);
        if (i == 8) { gt0 = bfr(acc[0]); gt1 = bfr(acc[2]); }
        if (i == 17) {
          if ((lane & 3) == 0) {
            __nv_bfloat16* hh = (__nv_bfloat16*)(smem + S_H);
            hh[row] = __float2bfloat16(bfr(__fdividef(gt0, 1.f + __expf(-gt0))) * bfr(acc[0]));
            hh[row + 8] = __float2bfloat16(bfr(__fdividef(gt1, 1.f + __expf(-gt1))) * bfr(acc[2]));
          }
          proxy_fence();
        }
        if (i >= 18 && (lane & 3) == 0) { float* yp = g_ypart + blockIdx.x * DM + (i - 18) * 64 + row; yp[0] = acc[0]; yp[8] = acc[2]; }
        bar_sync(1, 128);
        if (tid == 0 && i < 23) ffn_load(sb, mp, i + 4);
      }
      if (tid == 0) { signal(1); STAMP(5); }
    }
    if ((idx >> 6) == tg) {
      if (tid == 0) await(1, NSL);
      bar_sync(1, 128);
      float4* red = (float4*)(smem + S_FFN + 24 * KB);
      if (tid < 108) {
        const float4* yp = (const float4*)(g_ypart + (tid / 36) * 24 * DM + hg * 144) + tid % 36;
        float4 a = make_float4(0.f, 0.f, 0.f, 0.f);
        #pragma unroll 4
        for (int i = 0; i < 24; i++) { float4 b = __ldcg(yp + i * (DM / 4)); a.x += b.x; a.y += b.y; a.z += b.z; a.w += b.w; }
        red[tid] = a;
      }
      bar_sync(1, 128);
      const float rs = bfr(__fdividef(1.f, 1.f + __expf(-bfr(*(volatile float*)(smem + S_ST + 8)))));
      for (int i = tid; i < 144; i += 128) { const float* f = (const float*)red + i; ((float*)(smem + S_Y))[i] = bfr(bfr(f[0] + f[144] + f[288]) * rs); }
    }
    bar_arrive(5, 640);
    if (tid == 0) {
      #pragma unroll 1
      for (int u = 0; u < 9; u++) {
        const int c = u == 0 ? 5 : u < 6 ? u - 1 : u;
        if (c < 5) mbar_wait(sb + B_REL + (c + 1) * 8, 0);
        if (c > 5) mbar_wait(sb + B_E + (c - 6) * 8, 1);
        mbar_expect(sb + B_W + c * 8, 24576);
        #pragma unroll
        for (int j = 0; j < 3; j++) tma3(sb + wslotC(c) + j * 8192, &mp.wo, j * 64, hg, c * 64, sb + B_W + c * 8);
        if (u == 5) {
          await(8 + tg, 4);
          STAMP(18);
          #pragma unroll 1
          for (int k = 0; k < 9; k++) { mbar_expect(sb + B_X + k * 8, 8192); tma2(sb + oslot(k), &mp.o, k * 64, tg * 64, sb + B_X + k * 8); }
        }
      }
      unsigned old;
      asm volatile("atom.add.acq_rel.gpu.global.u32 %0, [%1], 1;" : "=r"(old) : "l"(g_cnt + 64) : "memory");
      if (old == NCTA - 1) {
        #pragma unroll 1
        for (int i = 0; i < 40; i++) g_cnt[i * 32] = 0;
      }
    }
  } else {
    asm volatile("setmaxnreg.inc.sync.aligned.u32 112;");
    const int warp = (threadIdx.x >> 5) & 3, lane = threadIdx.x & 31, g = lane >> 2, t = lane & 3;
    uint32_t* sq = (uint32_t*)(smem + S_Q) + (warp * 16 + g) * QP;
    if (wg == 0) {
      gemm<false, 0>(sb, sq + t);
      STAMP0(4);
    } else if (wg == 1) {
      gemm<false, 1>(sb, sq + t);
    } else if (wg == 3) {
      special(smem, sb, tg * 64 + hg * 16, hg * 16);
      if (threadIdx.x == 384) STAMP(2);
      bar_arrive(3, 416);
    }
    bar_sync(4, 544);
    STAMP0(7);
    volatile uint32_t* stash = (volatile uint32_t*)(smem + S_FLAG) + threadIdx.x;
    volatile uint8_t* fl = smem + S_FLAG - 512 + threadIdx.x;
    const uint32_t sb16 = sb >> 4;
    const int q0 = tg * 64 + warp * 16;
    uint32_t qa[8];
    stash[0] = 0; qa[6] = stash[0]; qa[7] = stash[0];
    {
      const float2 st = *(const float2*)(smem + S_ST);
      const bool kvbad = !(st.x <= 65536.f) || !(st.y <= 16384.f) || !(st.y >= 0.015625f);
      const float QS = 0.23570226f * 1.44269504f, kn = sqrta(st.x) * (QS * 1.01f * 8.f);
      uint32_t flags = 0;
      #pragma unroll
      for (int i = 1; i >= 0; i--) {
        const uint32_t* qp = sq + (i * 4 + wg) * 9;
        uint32_t raw[6] = {qp[t], qp[8 * QP + t], qp[t + 4], qp[8 * QP + t + 4], t == 0 ? qp[8] : 0u, t == 0 ? qp[8 * QP + 8] : 0u};
        float n[2] = {0.f, 0.f};
        #pragma unroll
        for (int j = 0; j < 6; j++) {
          float a = bflo(raw[j]), b = bfhi(raw[j]);
          n[j & 1] += a * a + b * b;
          qa[j] = pack2h(a * (QS / 32.f), b * (QS / 32.f));
        }
        #pragma unroll
        for (int r = 0; r < 2; r++) {
          n[r] += __shfl_xor_sync(~0u, n[r], 1); n[r] += __shfl_xor_sync(~0u, n[r], 2);
          float M = ceilf(sqrta(n[r]) * kn) * 0.125f;
          bool bad = kvbad || !(n[r] <= 65536.f) || !(M <= 40.f);
          if (bad) { flags |= 1u << (3 * i); M = 0.f; }
          if (M > 14.f) { flags |= 2u << (3 * i + r); M = 28.f - M; }
          if (t == 1) qa[4 + r] = pack2h(M, M - 13.f);
        }
        if (i) {
          #pragma unroll
          for (int j = 0; j < 6; j++) stash[j * 512] = qa[j];
        }
      }
      *fl = flags;
    }
    uint32_t s0[16], s1[16], p0[16], p1[16];
    mbar_wait(sb + B_KV, 0);
    wg_fence(); qk64(s0, qa, sb16); wg_commit();
    #pragma unroll
    for (int i = 0; i < 2; i++) {
      float o[12];
      #pragma unroll
      for (int k = 0; k < 12; k++) asm volatile("mov.b32 %0, 0;" : "=f"(o[k]));
      wg_wait<0>(); fence_regs<16>(s0);
      STAMP0(9 + 3 * i);
      #pragma unroll 1
      for (int c = 0; c < 8; c++) {
        const uint32_t a0 = sb16 + c * (CH >> 4), an = c == 7 ? sb16 : a0 + (CH >> 4);
        wg_fence(); qk64(s1, qa, a0 + 64); wg_commit();
        softmax64(s0, p0); fence_regs<16>(p0);
        wg_fence(); pv64(o, p0, a0); PVC qk64(s0, qa, a0 + 128); wg_commit();
        wg_wait<WN>(); fence_regs<16>(s1);
        if (i == 1 && lane == 0 && c) mbar_arrive(sb + B_REL + 8 * c - 8);
        softmax64(s1, p1); fence_regs<16>(p1);
        wg_fence(); pv64(o, p1, a0 + 64); PVC qk64(s1, qa, a0 + 192); wg_commit();
        wg_wait<WN>(); fence_regs<16>(s0);
        softmax64(s0, p0); fence_regs<16>(p0);
        if (i == 0 && c < 7) mbar_wait(sb + B_KV + 8 * c + 8, 0);
        wg_fence(); pv64(o, p0, a0 + 128); PVC qk64(s0, qa, an); wg_commit();
        wg_wait<WN>(); fence_regs<16>(s1);
        softmax64(s1, p1); fence_regs<16>(p1);
        wg_fence(); pv64(o, p1, a0 + 192); wg_commit();
        wg_wait<1>(); fence_regs<16>(s0);
      }
      wg_wait<0>();
      fence_regs<12>(o);
      RETID
      if (i == 0) {
        #pragma unroll
        for (int j = 0; j < 6; j++) qa[j] = stash[j * 512];
        stash[0] = 0; qa[6] = stash[0]; qa[7] = stash[0];
        wg_fence(); qk64(s0, qa, sb16); wg_commit();
      }
      STAMP0(10 + 3 * i);
      const uint32_t flags = *fl;
      float l0 = __shfl_sync(0xffffffffu, o[0], lane | 3), l1 = __shfl_sync(0xffffffffu, o[2], lane | 3);
      bool bad = ((flags >> (3 * i)) & 1) || !(l0 <= 3e38f) || !(l1 <= 3e38f) || !(l0 > 0.f) || !(l1 > 0.f)
                 || (((flags >> (3 * i + 1)) & 1) && l0 < 256.f) || (((flags >> (3 * i + 2)) & 1) && l1 < 256.f);
      if (__any_sync(0xffffffffu, bad)) *fl = flags | (64u << i);
      else {
        float r0 = __fdividef(1.f, l0), r1 = __fdividef(1.f, l1);
        uint32_t* op0 = (uint32_t*)(g_o + (size_t)(q0 + g) * DM + (hg * 8 + i * 4 + wg) * 18);
        uint32_t* op1 = op0 + 4 * DM;
        op0[t] = pack2(o[4] * r0, o[5] * r0); op1[t] = pack2(o[6] * r1, o[7] * r1);
        op0[t + 4] = pack2(o[8] * r0, o[9] * r0); op1[t + 4] = pack2(o[10] * r1, o[11] * r1);
        if (t == 2) { op0[8] = pack2(o[0] * r0, o[1] * r0); op1[8] = pack2(o[2] * r1, o[3] * r1); }
      }
    }
    {
    RETID
    uint32_t* sq2 = (uint32_t*)(smem + S_Q) + (warp * 16 + g) * QP;
    {
      const uint32_t flags = *fl;
      #pragma unroll 1
      for (int i = 0; i < 2; i++)
        if ((flags >> (6 + i)) & 1) attn_exact((const __nv_bfloat16*)(smem + S_Q) + warp * 32 * QP + (i * 4 + wg) * 18, q0, hg * 8 + i * 4 + wg, lane);
    }
    if ((tx_ & 127) == 0 && wg) STAMP(14 + wg);
    bar_sync(6, 512);
    if (tx_ == 384) signal(8 + tg);
    uint4 xr[3];
    #pragma unroll
    for (int u = 0; u < 3; u++) {
      const int v = tx_ + u * 512, row = v / 18, c8 = v % 18;
      if (v < 1152) xr[u] = ldg16(x + (size_t)(tg * 64 + row) * DM + hg * 144 + c8 * 8);
    }
    if (wg == 0) gemm<true, 0>(sb, sq2 + t);
    if (wg == 1) gemm<true, 1>(sb, sq2 + t);
    STAMP0(20);
    bar_sync(5, 640);
    const int li = *(const int*)(smem + S_ST + 12) - tg * 64;
    #pragma unroll
    for (int u = 0; u < 3; u++) {
      const int v = tx_ + u * 512, row = v / 18, c8 = v % 18;
      if (v < 1152) {
        const float gg = ((const float*)(smem + S_G))[row];
        const uint4 av = *(const uint4*)(smem + S_Q + row * (QP * 4) + c8 * 16);
        const uint32_t aa[4] = {av.x, av.y, av.z, av.w}, xx[4] = {xr[u].x, xr[u].y, xr[u].z, xr[u].w};
        uint32_t r[4];
        #pragma unroll
        for (int k = 0; k < 4; k++) {
          float b0 = bflo(xx[k]), b1 = bfhi(xx[k]);
          if (row == li) { const float* ys = (const float*)(smem + S_Y) + c8 * 8 + 2 * k; b0 += ys[0]; b1 += ys[1]; }
          r[k] = pack2(fmaf(gg, bflo(aa[k]) - b0, b0), fmaf(gg, bfhi(aa[k]) - b1, b1));
        }
        *(uint4*)(out + (size_t)(tg * 64 + row) * DM + hg * 144 + c8 * 8) = make_uint4(r[0], r[1], r[2], r[3]);
      }
    }
    }
    STAMP0(21);
  }
}

typedef CUresult (*EncFn)(CUtensorMap*, CUtensorMapDataType, cuuint32_t, void*, const cuuint64_t*, const cuuint64_t*, const cuuint32_t*, const cuuint32_t*,
                          CUtensorMapInterleave, CUtensorMapSwizzle, CUtensorMapL2promotion, CUtensorMapFloatOOBfill);
static void make_map(EncFn enc, CUtensorMap* m, const void* base, int cols, int rows, bool grouped) {
  cuuint64_t d2[2] = {(cuuint64_t)cols, (cuuint64_t)rows}, s2[1] = {(cuuint64_t)cols * 2}, d3[3] = {144, 4, (cuuint64_t)rows}, s3[2] = {288, (cuuint64_t)cols * 2};
  cuuint32_t b2[2] = {64, 64}, b3[3] = {64, 1, 64}, es[3] = {1, 1, 1};
  enc(m, CU_TENSOR_MAP_DATA_TYPE_BFLOAT16, grouped ? 3 : 2, (void*)base, grouped ? d3 : d2, grouped ? s3 : s2, grouped ? b3 : b2, es, CU_TENSOR_MAP_INTERLEAVE_NONE,
      CU_TENSOR_MAP_SWIZZLE_128B, CU_TENSOR_MAP_L2_PROMOTION_L2_256B, CU_TENSOR_MAP_FLOAT_OOB_FILL_NONE);
}

extern "C" void kernel_launch(void* const* d_in, const int* in_sizes, int n_in, void* d_out, int out_size) {
  typedef const __nv_bfloat16* P;
  static EncFn enc = nullptr;
  static void* po = nullptr;
  if (!enc) {
    cudaDriverEntryPointQueryResult qr;
    cudaGetDriverEntryPoint("cuTensorMapEncodeTiled", (void**)&enc, cudaEnableDefault, &qr);
    cudaGetSymbolAddress(&po, g_o);
    cudaFuncSetAttribute(k_fused, cudaFuncAttributeMaxDynamicSharedMemorySize, SMEM);
  }
  Maps mp;
  make_map(enc, &mp.x, d_in[0], DM, SEQ, false); make_map(enc, &mp.wq, d_in[1], DM, DM, true); make_map(enc, &mp.wo, d_in[4], DM, DM, true);
  make_map(enc, &mp.o, po, DM, SEQ, false); make_map(enc, &mp.wg, d_in[7], FF, DM, false); make_map(enc, &mp.wu, d_in[8], FF, DM, false);
  make_map(enc, &mp.wd, d_in[9], DM, FF, false);
  k_fused<<<NCTA, 640, SMEM, cudaStreamPerThread>>>(mp, (P)d_in[0], (P)d_in[2], (P)d_in[3], (P)d_in[6], (P)d_in[10], (__nv_bfloat16*)d_out);
}
```

```cpp
#include <cuda_runtime.h>
#include <cuda_bf16.h>
#include <cuda_fp16.h>
#include <stdint.h>
#include <cuda.h>

constexpr int SEQ = 2048, DM = 576, FF = 4608, NSL = 72, NCTA = 128;
constexpr uint32_t KMASK = 0x25;

__device__ __align__(128) __nv_bfloat16 g_o[SEQ * DM];
__device__ uint4 g_kv[5 * SEQ];
__device__ float g_kraw[SEQ * 18];
__device__ float g_vraw[SEQ * 18];
__device__ float g_gate[SEQ];
__device__ float4 g_stat[NCTA];
__device__ float g_ypart[NSL * DM];
__device__ unsigned g_cnt[40 * 32];

#define STAMP(k)
#define STAMP0(k)
__device__ __forceinline__ void wgh_n64_sd0(uint32_t* d, uint32_t a0, uint32_t a1, uint32_t a2, uint32_t a3, uint64_t bdesc) {
  asm volatile("{\n.reg .pred p;\nsetp.ne.b32 p, 0, 0;\n"
    "wgmma.mma_async.sync.aligned.m64n64k16.f16.f16.f16 {%0, %1, %2, %3, %4, %5, %6, %7, %8, %9, %10, %11, %12, %13, %14, %15}, {%16, %17, %18, %19}, %20, p, 1, 1, 0;\n}\n"
    : "=r"(d[0]), "=r"(d[1]), "=r"(d[2]), "=r"(d[3]), "=r"(d[4]), "=r"(d[5]), "=r"(d[6]), "=r"(d[7]), "=r"(d[8]), "=r"(d[9]), "=r"(d[10]), "=r"(d[11]), "=r"(d[12]), "=r"(d[13]), "=r"(d[14]), "=r"(d[15]) : "r"(a0), "r"(a1), "r"(a2), "r"(a3), "l"(bdesc));
}
__device__ __forceinline__ void wgh_n64_sd1(uint32_t* d, uint32_t a0, uint32_t a1, uint32_t a2, uint32_t a3, uint64_t bdesc) {
  asm volatile("{\n.reg .pred p;\nsetp.ne.b32 p, 1, 0;\n"
    "wgmma.mma_async.sync.aligned.m64n64k16.f16.f16.f16 {%0, %1, %2, %3, %4, %5, %6, %7, %8, %9, %10, %11, %12, %13, %14, %15}, {%16, %17, %18, %19}, %20, p, 1, 1, 0;\n}\n"
    : "+r"(d[0]), "+r"(d[1]), "+r"(d[2]), "+r"(d[3]), "+r"(d[4]), "+r"(d[5]), "+r"(d[6]), "+r"(d[7]), "+r"(d[8]), "+r"(d[9]), "+r"(d[10]), "+r"(d[11]), "+r"(d[12]), "+r"(d[13]), "+r"(d[14]), "+r"(d[15]) : "r"(a0), "r"(a1), "r"(a2), "r"(a3), "l"(bdesc));
}
__device__ __forceinline__ void wg_pv(float* d, uint32_t a0, uint32_t a1, uint32_t a2, uint32_t a3, uint64_t bdesc) {
  asm volatile("{\n.reg .pred p;\nsetp.ne.b32 p, 1, 0;\n"
    "wgmma.mma_async.sync.aligned.m64n24k16.f32.f16.f16 {%0, %1, %2, %3, %4, %5, %6, %7, %8, %9, %10, %11}, {%12, %13, %14, %15}, %16, p, 1, 1, 1;\n}\n"
    : "+f"(d[0]), "+f"(d[1]), "+f"(d[2]), "+f"(d[3]), "+f"(d[4]), "+f"(d[5]), "+f"(d[6]), "+f"(d[7]), "+f"(d[8]), "+f"(d[9]), "+f"(d[10]), "+f"(d[11]) : "r"(a0), "r"(a1), "r"(a2), "r"(a3), "l"(bdesc));
}
__device__ __forceinline__ void wg_ss64(float* d, uint64_t adesc, uint64_t bdesc) {
  asm volatile("{\n.reg .pred p;\nsetp.ne.b32 p, 1, 0;\n"
    "wgmma.mma_async.sync.aligned.m64n64k16.f32.bf16.bf16 {%0, %1, %2, %3, %4, %5, %6, %7, %8, %9, %10, %11, %12, %13, %14, %15, %16, %17, %18, %19, %20, %21, %22, %23, %24, %25, %26, %27, %28, %29, %30, %31}, %32, %33, p, 1, 1, 0, 1;\n}\n"
    : "+f"(d[0]), "+f"(d[1]), "+f"(d[2]), "+f"(d[3]), "+f"(d[4]), "+f"(d[5]), "+f"(d[6]), "+f"(d[7]), "+f"(d[8]), "+f"(d[9]), "+f"(d[10]), "+f"(d[11]), "+f"(d[12]), "+f"(d[13]), "+f"(d[14]), "+f"(d[15]), "+f"(d[16]), "+f"(d[17]), "+f"(d[18]), "+f"(d[19]), "+f"(d[20]), "+f"(d[21]), "+f"(d[22]), "+f"(d[23]), "+f"(d[24]), "+f"(d[25]), "+f"(d[26]), "+f"(d[27]), "+f"(d[28]), "+f"(d[29]), "+f"(d[30]), "+f"(d[31]) : "l"(adesc), "l"(bdesc));
}
__device__ __forceinline__ void wg_ss80(float* d, uint64_t adesc, uint64_t bdesc) {
  asm volatile("{\n.reg .pred p;\nsetp.ne.b32 p, 1, 0;\n"
    "wgmma.mma_async.sync.aligned.m64n80k16.f32.bf16.bf16 {%0, %1, %2, %3, %4, %5, %6, %7, %8, %9, %10, %11, %12, %13, %14, %15, %16, %17, %18, %19, %20, %21, %22, %23, %24, %25, %26, %27, %28, %29, %30, %31, %32, %33, %34, %35, %36, %37, %38, %39}, %40, %41, p, 1, 1, 0, 1;\n}\n"
    : "+f"(d[0]), "+f"(d[1]), "+f"(d[2]), "+f"(d[3]), "+f"(d[4]), "+f"(d[5]), "+f"(d[6]), "+f"(d[7]), "+f"(d[8]), "+f"(d[9]), "+f"(d[10]), "+f"(d[11]), "+f"(d[12]), "+f"(d[13]), "+f"(d[14]), "+f"(d[15]), "+f"(d[16]), "+f"(d[17]), "+f"(d[18]), "+f"(d[19]), "+f"(d[20]), "+f"(d[21]), "+f"(d[22]), "+f"(d[23]), "+f"(d[24]), "+f"(d[25]), "+f"(d[26]), "+f"(d[27]), "+f"(d[28]), "+f"(d[29]), "+f"(d[30]), "+f"(d[31]), "+f"(d[32]), "+f"(d[33]), "+f"(d[34]), "+f"(d[35]), "+f"(d[36]), "+f"(d[37]), "+f"(d[38]), "+f"(d[39]) : "l"(adesc), "l"(bdesc));
}
__device__ __forceinline__ void wg_ss8(float* d, uint64_t adesc, uint64_t bdesc) {
  asm volatile("{\n.reg .pred p;\nsetp.ne.b32 p, 1, 0;\n"
    "wgmma.mma_async.sync.aligned.m64n8k16.f32.bf16.bf16 {%0, %1, %2, %3}, %4, %5, p, 1, 1, 1, 0;\n}\n"
    : "+f"(d[0]), "+f"(d[1]), "+f"(d[2]), "+f"(d[3]) : "l"(adesc), "l"(bdesc));
}

__device__ __forceinline__ void wg_fence() { asm volatile("wgmma.fence.sync.aligned;" ::: "memory"); }
__device__ __forceinline__ void wg_commit() { asm volatile("wgmma.commit_group.sync.aligned;" ::: "memory"); }
template<int N> __device__ __forceinline__ void wg_wait() { asm volatile("wgmma.wait_group.sync.aligned %0;" :: "n"(N) : "memory"); }
__device__ __forceinline__ uint32_t pack2(float lo, float hi) { uint32_t r; asm("cvt.rn.bf16x2.f32 %0, %1, %2;" : "=r"(r) : "f"(hi), "f"(lo)); return r; }
__device__ __forceinline__ uint32_t pack2h(float lo, float hi) { uint32_t r; asm("cvt.rn.f16x2.f32 %0, %1, %2;" : "=r"(r) : "f"(hi), "f"(lo)); return r; }
__device__ __forceinline__ float bflo(uint32_t v) { return __uint_as_float(v << 16); }
__device__ __forceinline__ float bfhi(uint32_t v) { return __uint_as_float(v & 0xffff0000u); }
__device__ __forceinline__ float bfr(float v) { return __bfloat162float(__float2bfloat16(v)); }
__device__ __forceinline__ uint32_t hfma2(uint32_t a, uint32_t b, uint32_t c) { uint32_t r; asm("fma.rn.f16x2 %0, %1, %2, %3;" : "=r"(r) : "r"(a), "r"(b), "r"(c)); return r; }
__device__ __forceinline__ uint32_t hfma2r(uint32_t a, uint32_t b, uint32_t c) { uint32_t r; asm("fma.rn.relu.f16x2 %0, %1, %2, %3;" : "=r"(r) : "r"(a), "r"(b), "r"(c)); return r; }
__device__ __forceinline__ uint32_t ex2h2(uint32_t x) { uint32_t r; asm("ex2.approx.f16x2 %0, %1;" : "=r"(r) : "r"(x)); return r; }
__device__ __forceinline__ uint64_t mk64(uint32_t lo, uint32_t hi) { uint64_t d; asm("mov.b64 %0, {%1, %2};" : "=l"(d) : "r"(lo), "r"(hi)); return d; }
template<int N> __device__ __forceinline__ void fence_regs(float* r) {
  #pragma unroll
  for (int i = 0; i < N; i++) asm volatile("" : "+f"(r[i]) :: "memory");
}
template<int N> __device__ __forceinline__ void fence_regs(uint32_t* r) {
  #pragma unroll
  for (int i = 0; i < N; i++) asm volatile("" : "+r"(r[i]) :: "memory");
}
__device__ __forceinline__ void cp16(uint32_t dst, const void* src) { asm volatile("cp.async.cg.shared.global [%0], [%1], 16;" :: "r"(dst), "l"(src) : "memory"); }
__device__ __forceinline__ void cp4(uint32_t dst, const void* src) { asm volatile("cp.async.ca.shared.global [%0], [%1], 4;" :: "r"(dst), "l"(src) : "memory"); }
__device__ __forceinline__ void cp_commit() { asm volatile("cp.async.commit_group;" ::: "memory"); }
template<int N> __device__ __forceinline__ void cp_wait() { asm volatile("cp.async.wait_group %0;" :: "n"(N) : "memory"); }
__device__ __forceinline__ void proxy_fence() { asm volatile("fence.proxy.async.shared::cta;" ::: "memory"); }
__device__ __forceinline__ void pdl_wait() { asm volatile("griddepcontrol.wait;" ::: "memory"); }
__device__ __forceinline__ void pdl_go() { asm volatile("griddepcontrol.launch_dependents;" ::: "memory"); }
__device__ __forceinline__ uint4 ldg16(const void* p) { uint4 v; asm volatile("ld.global.nc.L1::no_allocate.v4.u32 {%0,%1,%2,%3}, [%4];" : "=r"(v.x), "=r"(v.y), "=r"(v.z), "=r"(v.w) : "l"(p)); return v; }
__device__ __forceinline__ uint4 ldg16c(const void* p) { uint4 v; asm volatile("ld.global.L1::no_allocate.v4.u32 {%0,%1,%2,%3}, [%4];" : "=r"(v.x), "=r"(v.y), "=r"(v.z), "=r"(v.w) : "l"(p) : "memory"); return v; }
__device__ __forceinline__ void mbar_wait(uint32_t bar, uint32_t parity) {
  #pragma unroll 1
  for (int it = 0; it < (1 << 22); it++) {
    uint32_t ok;
    asm volatile("{\n.reg .pred p;\nmbarrier.try_wait.parity.shared::cta.b64 p, [%1], %2;\nselp.u32 %0, 1, 0, p;\n}\n" : "=r"(ok) : "r"(bar), "r"(parity) : "memory");
    if (ok) break;
  }
}
__device__ __forceinline__ void mbar_init(uint32_t bar, uint32_t cnt) { asm volatile("mbarrier.init.shared::cta.b64 [%0], %1;" :: "r"(bar), "r"(cnt) : "memory"); }
__device__ __forceinline__ void mbar_expect(uint32_t bar, uint32_t bytes) { asm volatile("mbarrier.arrive.expect_tx.shared::cta.b64 _, [%0], %1;" :: "r"(bar), "r"(bytes) : "memory"); }
__device__ __forceinline__ void mbar_arrive(uint32_t bar) { asm volatile("mbarrier.arrive.shared::cta.b64 _, [%0];" :: "r"(bar) : "memory"); }
__device__ __forceinline__ void tma2(uint32_t dst, const CUtensorMap* m, int c0, int c1, uint32_t bar) {
  asm volatile("cp.async.bulk.tensor.2d.shared::cluster.global.mbarrier::complete_tx::bytes [%0], [%1, {%3, %4}], [%2];" :: "r"(dst), "l"(m), "r"(bar), "r"(c0), "r"(c1) : "memory");
}
__device__ __forceinline__ void tma3(uint32_t dst, const CUtensorMap* m, int c0, int c1, int c2, uint32_t bar) {
  asm volatile("cp.async.bulk.tensor.3d.shared::cluster.global.mbarrier::complete_tx::bytes [%0], [%1, {%3, %4, %5}], [%2];" :: "r"(dst), "l"(m), "r"(bar), "r"(c0), "r"(c1), "r"(c2) : "memory");
}
__device__ __forceinline__ void bulk(uint32_t dst, const void* src, uint32_t bytes, uint32_t bar) {
  asm volatile("cp.async.bulk.shared::cluster.global.mbarrier::complete_tx::bytes [%0], [%1], %2, [%3];" :: "r"(dst), "l"(src), "r"(bytes), "r"(bar) : "memory");
}
__device__ __forceinline__ void tma3m(uint32_t dst, const CUtensorMap* m, int c0, int c1, int c2, uint32_t bar) {
  asm volatile("cp.async.bulk.tensor.3d.shared::cluster.global.mbarrier::complete_tx::bytes.multicast::cluster [%0], [%1, {%3, %4, %5}], [%2], %6;" :: "r"(dst), "l"(m), "r"(bar), "r"(c0), "r"(c1), "r"(c2), "h"((uint16_t)3) : "memory");
}
__device__ __forceinline__ void bulkm(uint32_t dst, const void* src, uint32_t bytes, uint32_t bar) {
  asm volatile("cp.async.bulk.shared::cluster.global.mbarrier::complete_tx::bytes.multicast::cluster [%0], [%1], %2, [%3], %4;" :: "r"(dst), "l"(src), "r"(bytes), "r"(bar), "h"((uint16_t)3) : "memory");
}
__device__ __forceinline__ void mbar_arrive_at(uint32_t bar, uint32_t rank) {
  asm volatile("{\n.reg .b32 a;\nmapa.shared::cluster.u32 a, %0, %1;\nmbarrier.arrive.release.cluster.shared::cluster.b64 _, [a];\n}" :: "r"(bar), "r"(rank) : "memory");
}
__device__ __forceinline__ void bar_sync(int id, int n) { asm volatile("bar.sync %0, %1;" :: "r"(id), "r"(n) : "memory"); }
__device__ __forceinline__ void bar_arrive(int id, int n) { asm volatile("bar.arrive %0, %1;" :: "r"(id), "r"(n) : "memory"); }
__device__ __forceinline__ void proxy_fence_all() { asm volatile("fence.proxy.async;" ::: "memory"); }
__device__ __forceinline__ void signal(int i) {
  proxy_fence_all();
  asm volatile("fence.acq_rel.gpu;\nred.relaxed.gpu.global.add.u32 [%0], 1;" :: "l"(g_cnt + i * 32) : "memory");
}
__device__ __forceinline__ void await(int i, unsigned n) {
  #pragma unroll 1
  for (int it = 0; it < (1 << 21); it++) {
    unsigned v; asm volatile("ld.acquire.gpu.global.u32 %0, [%1];" : "=r"(v) : "l"(g_cnt + i * 32) : "memory");
    if (v >= n) break;
  }
  proxy_fence_all();
}
__device__ __forceinline__ void ldsm4(uint32_t a, uint32_t* r) {
  asm volatile("ldmatrix.sync.aligned.m8n8.x4.shared.b16 {%0,%1,%2,%3}, [%4];" : "=r"(r[0]), "=r"(r[1]), "=r"(r[2]), "=r"(r[3]) : "r"(a) : "memory");
}
__device__ __forceinline__ void mma16(float* d, const uint32_t* a, uint32_t b0, uint32_t b1) {
  asm volatile("mma.sync.aligned.m16n8k16.row.col.f32.bf16.bf16.f32 {%0,%1,%2,%3}, {%4,%5,%6,%7}, {%8,%9}, {%0,%1,%2,%3};"
    : "+f"(d[0]), "+f"(d[1]), "+f"(d[2]), "+f"(d[3]) : "r"(a[0]), "r"(a[1]), "r"(a[2]), "r"(a[3]), "r"(b0), "r"(b1));
}

constexpr uint32_t KB = 1024, CH = 20480;
constexpr uint32_t S_X = 44 * KB, S_W = 116 * KB;
constexpr uint32_t S_FFN = 160 * KB, S_Q = 192 * KB, S_FLAG = 212 * KB, S_BAR = 224 * KB;
constexpr uint32_t B_X = S_BAR, B_W = B_X + 72, B_E = B_W + 72, B_R = B_E + 48, B_P = B_R + 8, B_KV = B_P + 8, B_REL = B_KV + 64, B_F = B_REL + 56;
constexpr uint32_t S_ST = S_BAR + 368, S_G = S_BAR + 384, S_Y = S_G + 256, S_H = S_Y + 576, S_XS = S_H + 128, SMEM = S_XS + 1152 + 128;
constexpr int QP = 76;
__device__ __forceinline__ uint32_t wslotA(int c) { return S_W + (c & 3) * 24 * KB; }
__device__ __forceinline__ uint32_t wslotC(int c) { return c == 5 ? S_FFN : (c < 5 ? c : c - 6) * 24 * KB; }
__device__ __forceinline__ uint32_t oslot(int c) { return (c < 5 ? 120 + 8 * c : 152 + 8 * c) * KB; }

template<bool C, int W> __device__ __forceinline__ void gemm(uint32_t sb, uint32_t* sq) {
  constexpr int NA = W ? 40 : 32;
  float acc[NA];
  #pragma unroll
  for (int i = 0; i < NA; i++) asm volatile("mov.b32 %0, 0;" : "=f"(acc[i]));
  const uint32_t hi = 64u | (1u << 30);
  #pragma unroll
  for (int c = 0; c < 9; c++) {
    const uint32_t alo = (((sb & 0x3FFFF) + (C ? oslot(c) : S_X + c * 8192)) >> 4) | (1u << 16), blo = (((sb & 0x3FFFF) + (C ? wslotC(c) : wslotA(c)) + W * 8192) >> 4) | (512u << 16);
    mbar_wait(sb + B_X + c * 8, C);
    mbar_wait(sb + B_W + c * 8, C);
    wg_fence();
    #pragma unroll
    for (int k = 0; k < 4; k++) { if (W) wg_ss80(acc, mk64(alo + k * 2, hi), mk64(blo + k * 128, hi)); else wg_ss64(acc, mk64(alo + k * 2, hi), mk64(blo + k * 128, hi)); }
    wg_commit();
    if (c >= 1 && c <= (C ? 3 : 5)) { wg_wait<1>(); if ((threadIdx.x & 31) == 0) { if (C) mbar_arrive(sb + B_E + (c + 2) * 8); else mbar_arrive_at(sb + B_E + ((c - 1) >> 1) * 8, (c - 1) & 1); } }
  }
  wg_wait<0>();
  fence_regs<NA>(acc);
  if (C) bar_sync(7, 256); else bar_sync(3, 416);
  #pragma unroll
  for (int j = 0; j < NA / 4; j++) { sq[W * 32 + j * 4] = pack2(acc[4*j], acc[4*j+1]); sq[8 * QP + W * 32 + j * 4] = pack2(acc[4*j+2], acc[4*j+3]); }
}

__device__ __forceinline__ void special(uint8_t* smem, uint32_t sb, int tok0, int row0) {
  const int tid = threadIdx.x & 127, warp = tid >> 5, lane = tid & 31, g = lane >> 2, t = lane & 3;
  float acc[6][4];
  #pragma unroll
  for (int i = 0; i < 6; i++) { acc[i][0] = acc[i][1] = acc[i][2] = acc[i][3] = 0.f; }
  const uint32_t* raw = (const uint32_t*)smem;
  const int r = row0 + (lane & 15);
  const uint32_t xa = sb + S_X + r * 128 + (((warp * 2 + (lane >> 4)) ^ (r & 7)) << 4);
  const int kb = warp * 16 + 2 * t;
  const uint32_t* pk = raw + kb * 9 + g;
  const uint32_t* pl = g < 2 ? raw + g * 5184 + kb * 9 + 8 : raw + 10368 + (g & 1) * 288 + (kb >> 1);
  const int ls = g < 2 ? 9 : 0, lc = g < 2 ? 576 : 32, l8 = g < 2 ? 72 : 4;
  const uint32_t se = g < 2 ? 0x5410 : 0x3210;
  mbar_wait(sb + B_R, 0);
  if (tid == 0) STAMP(1);
  #pragma unroll
  for (int c = 0; c < 9; c++) {
    uint32_t a[4];
    mbar_wait(sb + B_X + c * 8, 0);
    ldsm4(xa + c * 8192, a);
    #pragma unroll
    for (int m = 0; m < 2; m++) {
      const uint32_t* p = pk + m * 5184 + c * 576;
      uint32_t w0 = p[0], w1 = p[9], w2 = p[72], w3 = p[81];
      mma16(acc[2*m], a, __byte_perm(w0, w1, 0x5410), __byte_perm(w2, w3, 0x5410));
      mma16(acc[2*m+1], a, __byte_perm(w0, w1, 0x7632), __byte_perm(w2, w3, 0x7632));
    }
    const uint32_t* p = pl + c * lc;
    uint32_t w0 = p[0], w1 = p[ls], w2 = p[l8], w3 = p[l8 + ls];
    mma16(acc[4], a, __byte_perm(w0, w1, se), __byte_perm(w2, w3, se));
    mma16(acc[5], a, __byte_perm(w0, w1, 0x7632), __byte_perm(w2, w3, 0x7632));
  }
  if (tid == 0) STAMP(6);
  bar_sync(2, 128);
  float* part = (float*)smem;
  #pragma unroll
  for (int h = 0; h < 2; h++) {
    float* q = part + (warp * 16 + g + h * 8) * 44;
    *(float4*)(q + 4 * t) = make_float4(acc[0][2*h], acc[1][2*h], acc[0][2*h+1], acc[1][2*h+1]);
    *(float4*)(q + 16 + 4 * t) = make_float4(acc[2][2*h], acc[3][2*h], acc[2][2*h+1], acc[3][2*h+1]);
    if (t < 2) *(float2*)(q + 32 + 2 * t) = make_float2(acc[4][2*h], acc[4][2*h+1]);
    if (t == 0) *(float2*)(q + 36) = make_float2(acc[5][2*h], acc[5][2*h+1]);
  }
  bar_sync(2, 128);
  #pragma unroll
  for (int i = tid; i < 176; i += 128) {
    float4 a = ((float4*)part)[i], b = ((float4*)part)[i + 176], c = ((float4*)part)[i + 352], d = ((float4*)part)[i + 528];
    ((float4*)part)[i] = make_float4((a.x + b.x) + (c.x + d.x), (a.y + b.y) + (c.y + d.y), (a.z + b.z) + (c.z + d.z), (a.w + b.w) + (c.w + d.w));
  }
  bar_sync(2, 128);
  if (warp == 0) {
    const int isv = lane >> 4, key = tok0 + (lane & 15);
    const float* q = part + (lane & 15) * 44;
    float v[18];
    #pragma unroll
    for (int d = 0; d < 16; d++) v[d] = bfr(q[isv * 16 + d]);
    v[16] = bfr(q[32 + isv]); v[17] = bfr(q[36 + isv]);
    const bool mufu = (KMASK >> ((key >> 3) & 7)) & 1;
    const float sc = isv ? 1.f : mufu ? 32.f : 0.0625f;
    uint4* kv = g_kv + (key >> 8) * 1280 + (key & 255) + isv * 768;
    kv[0] = make_uint4(pack2h(v[0] * sc, v[1] * sc), pack2h(v[2] * sc, v[3] * sc), pack2h(v[4] * sc, v[5] * sc), pack2h(v[6] * sc, v[7] * sc));
    kv[256] = make_uint4(pack2h(v[8] * sc, v[9] * sc), pack2h(v[10] * sc, v[11] * sc), pack2h(v[12] * sc, v[13] * sc), pack2h(v[14] * sc, v[15] * sc));
    ((uint2*)(kv + 512 - isv * 768))[isv] = make_uint2(pack2h(v[16] * sc, v[17] * sc), isv ? 0x00003C00u : mufu ? 0x3C000000u : 0x00001800u);
    float s = 0.f, z = 0.f;
    #pragma unroll
    for (int d = 0; d < 18; d++) { (isv ? g_vraw : g_kraw)[d * SEQ + key] = v[d]; s = isv ? fmaxf(s, fabsf(v[d])) : fmaf(v[d], v[d], s); z = fmaf(v[d], 0.f, z); }
    s += z;
    if (!(s <= 3e38f)) s = 3e38f;
    if (isv) g_gate[key] = __fdividef(1.f, 1.f + __expf(-bfr(q[35])));
    float rr = q[34]; int ri = key;
    #pragma unroll
    for (int o = 8; o; o >>= 1) {
      s = fmaxf(s, __shfl_xor_sync(~0u, s, o));
      float r2 = __shfl_xor_sync(~0u, rr, o); int i2 = __shfl_xor_sync(~0u, ri, o);
      if (r2 > rr || (r2 == rr && i2 < ri)) { rr = r2; ri = i2; }
    }
    const float vm = __shfl_xor_sync(~0u, s, 16);
    if (lane == 0) g_stat[tok0 >> 4] = make_float4(s, vm, rr, __int_as_float(ri));
    __syncwarp();
    if (lane == 0) STAMP(8);
    if (lane == 0) signal(0);
  }
}
__device__ __forceinline__ bool elect() { uint32_t p; asm volatile("{\n.reg .pred q;\nelect.sync _|q, 0xffffffff;\nselp.u32 %0, 1, 0, q;\n}" : "=r"(p)); return p; }
__device__ __forceinline__ float sqrta(float x) { float r; asm("sqrt.approx.f32 %0, %1;" : "=f"(r) : "f"(x)); return r; }
__device__ __forceinline__ uint32_t ex2poly(uint32_t x) {
  uint32_t t = hfma2r(x, 0x02000200u, 0u);
  uint32_t u = hfma2(t, 0xF800F800u, x);
  uint32_t e = hfma2r(u, 0x47AC47ACu, 0x29A029A0u);
  uint32_t p = hfma2(e, u, 0x08000800u);
  return p + __funnelshift_l(t, t, 10);
}
__device__ __forceinline__ void softmax64(const uint32_t* s, uint32_t* p) {
  #pragma unroll
  for (int j = 0; j < 8; j++) {
    if ((KMASK >> j) & 1) { p[2*j] = ex2h2(s[2*j]); p[2*j+1] = ex2h2(s[2*j+1]); }
    else { p[2*j] = ex2poly(s[2*j]); p[2*j+1] = ex2poly(s[2*j+1]); }
  }
}
__device__ __forceinline__ uint32_t kvt(int j) { return (j >> 2) * (CH >> 4) + (j & 3) * 64; }
__device__ __forceinline__ void qk64(uint32_t* s, const uint32_t* q, uint32_t a16) {
  uint32_t lo = a16 | (256u << 16);
  wgh_n64_sd0(s, q[0], q[1], q[2], q[3], mk64(lo, 8));
  wgh_n64_sd1(s, q[4], q[5], q[6], q[7], mk64(lo + 512, 8));
}
__device__ __forceinline__ void pv64(float* o, const uint32_t* p, uint32_t a16) {
  uint32_t lo = (a16 | (8u << 16)) + 512;
  #pragma unroll
  for (int j = 0; j < 4; j++) wg_pv(o, p[4*j], p[4*j+1], p[4*j+2], p[4*j+3], mk64(lo + j * 16, 256));
}
__device__ __forceinline__ void attn_exact(const __nv_bfloat16* sq, int q0, int h, int lane) {
  #pragma unroll 1
  for (int r = 0; r < 16; r++) {
    float q[18], o[18];
    #pragma unroll
    for (int d = 0; d < 18; d++) { q[d] = __bfloat162float(sq[r * 2 * QP + d]) * 0.23570226f; o[d] = 0.f; }
    float m = -INFINITY;
    #pragma unroll 1
    for (int k = lane; k < SEQ; k += 32) {
      float s = 0.f;
      #pragma unroll
      for (int d = 0; d < 18; d++) s = fmaf(q[d], __ldcg(g_kraw + d * SEQ + k), s);
      m = fmaxf(m, s);
    }
    #pragma unroll
    for (int x = 16; x; x >>= 1) m = fmaxf(m, __shfl_xor_sync(~0u, m, x));
    float l = 0.f;
    #pragma unroll 1
    for (int k = lane; k < SEQ; k += 32) {
      float s = 0.f;
      #pragma unroll
      for (int d = 0; d < 18; d++) s = fmaf(q[d], __ldcg(g_kraw + d * SEQ + k), s);
      float p = __expf(s - m);
      l += p;
      #pragma unroll
      for (int d = 0; d < 18; d++) o[d] = fmaf(p, __ldcg(g_vraw + d * SEQ + k), o[d]);
    }
    #pragma unroll
    for (int x = 16; x; x >>= 1) {
      l += __shfl_xor_sync(~0u, l, x);
      #pragma unroll
      for (int d = 0; d < 18; d++) o[d] += __shfl_xor_sync(~0u, o[d], x);
    }
    float inv = __fdividef(1.f, l), mine = 0.f;
    #pragma unroll
    for (int d = 0; d < 18; d++) if (lane == d) mine = o[d];
    if (lane < 18) g_o[(size_t)(q0 + r) * DM + h * 18 + lane] = __float2bfloat16(mine * inv);
  }
}

struct Maps { CUtensorMap x, wq, wo, o, wg, wu, wd; };

__device__ __forceinline__ void ffn_load(uint32_t sb, const Maps& mp, int i) {
  const uint32_t bar = sb + B_F + (i & 3) * 8, dst = sb + S_FFN + (i & 3) * 8192;
  mbar_expect(bar, 8192);
  if (i < 18) tma2(dst, i < 9 ? &mp.wg : &mp.wu, blockIdx.x * 64, (i < 9 ? i : i - 9) * 64, bar);
  else tma2(dst, &mp.wd, (i - 18) * 64, blockIdx.x * 64, bar);
}

#define RETID uint32_t tx_; asm volatile("mov.u32 %0, %%tid.x;" : "=r"(tx_)); const int warp = (tx_ >> 5) & 3, lane = tx_ & 31, g = lane >> 2, t = lane & 3, wg = tx_ >> 7, q0 = tg * 64 + warp * 16; \
  volatile uint32_t* stash = (volatile uint32_t*)(smem + S_FLAG) + tx_; volatile uint8_t* fl = smem + S_FLAG - 512 + tx_; (void)g; (void)t; (void)q0; (void)stash; (void)fl; (void)wg;
#define PVC wg_commit();
#define WN 2
__global__ void __cluster_dims__(2, 1, 1) __launch_bounds__(640, 1) k_fused(const __grid_constant__ Maps mp, const __nv_bfloat16* __restrict__ x, const __nv_bfloat16* __restrict__ wk,
    const __nv_bfloat16* __restrict__ wv, const __nv_bfloat16* __restrict__ wr, const __nv_bfloat16* __restrict__ gw, __nv_bfloat16* __restrict__ out) {
  extern __shared__ __align__(1024) uint8_t smem[];
  const uint32_t sb = (uint32_t)__cvta_generic_to_shared(smem);
  const int wg = __shfl_sync(0xffffffffu, threadIdx.x >> 7, 0);
  const int rk = blockIdx.x & 1, tg = (blockIdx.x >> 3) * 2 + rk, hg = (blockIdx.x >> 1) & 3;
  STAMP0(0);
  if (threadIdx.x == 512) {
    #pragma unroll 1
    for (uint32_t b = B_X; b < B_F + 32; b += 8) mbar_init(sb + b, (b >= B_E + 24 && b < B_R) ? 8 : ((b >= B_REL && b < B_F) || (b >= B_E && b < B_R)) ? 16 : b == B_P ? 2 : 1);
    asm volatile("fence.mbarrier_init.release.cluster;" ::: "memory");
    proxy_fence();
    #pragma unroll 1
    for (int c = 0; c < 9; c++) { mbar_expect(sb + B_X + c * 8, 8192); tma2(sb + S_X + c * 8192, &mp.x, c * 64, tg * 64, sb + B_X + c * 8); }
    mbar_expect(sb + B_R, 43776);
    #pragma unroll 1
    for (int c = 0; c < 9; c++) mbar_expect(sb + B_W + c * 8, 24576);
    #pragma unroll 1
    for (int c = 0; c < 8; c++) mbar_expect(sb + B_KV + c * 8, CH);
  }
  __syncwarp();
  asm volatile("barrier.cluster.arrive.release.aligned;\nbarrier.cluster.wait.acquire.aligned;" ::: "memory");
  if (wg == 4) {
    asm volatile("setmaxnreg.dec.sync.aligned.u32 32;");
    const int tid = threadIdx.x - 512, warp = tid >> 5, lane = tid & 31;
    if (tid == 0) {
      bulkm(sb + rk * 20736, rk ? wv : wk, 20736, sb + B_R); bulkm(sb + 41472 + rk * 1152, rk ? gw : wr, 1152, sb + B_R);
      #pragma unroll 1
      for (int c = rk; c < 9; c += 2) {
        if (c >= 4) mbar_wait(sb + B_E + ((c - 4) >> 1) * 8, 0);
        #pragma unroll
        for (int j = 0; j < 3; j++) tma3m(sb + wslotA(c) + j * 8192, &mp.wq, j * 64, hg, c * 64, sb + B_W + c * 8);
      }
    } else if (warp == 1) {
      if (lane == 0) {
        await(0, NCTA);
        STAMP(3);
        #pragma unroll
        for (int c = 0; c < 2; c++) bulkm(sb + c * CH + rk * (CH / 2), g_kv + c * 1280 + rk * 640, CH / 2, sb + B_KV + c * 8);
      }
      __syncwarp();
      float k2 = 0.f, vm = 0.f, r = -INFINITY; int ri = 0;
      #pragma unroll
      for (int i = 0; i < 4; i++) {
        float4 s = __ldcg(g_stat + i * 32 + lane);
        k2 = fmaxf(k2, s.x); vm = fmaxf(vm, s.y);
        if (s.z > r) { r = s.z; ri = __float_as_int(s.w); }
      }
      const float2 gt = __ldcg((const float2*)(g_gate + tg * 64) + lane);
      bar_sync(3, 416);
      if (lane == 0) {
        mbar_arrive_at(sb + B_P, 0); mbar_arrive_at(sb + B_P, 1);
      }
      #pragma unroll
      for (int o = 16; o; o >>= 1) {
        k2 = fmaxf(k2, __shfl_xor_sync(~0u, k2, o)); vm = fmaxf(vm, __shfl_xor_sync(~0u, vm, o));
        float r2 = __shfl_xor_sync(~0u, r, o); int i2 = __shfl_xor_sync(~0u, ri, o);
        if (r2 > r || (r2 == r && i2 < ri)) { r = r2; ri = i2; }
      }
      if (lane == 0) *(float4*)(smem + S_ST) = make_float4(k2, vm, r, __int_as_float(ri & (SEQ - 1)));
      ((float2*)(smem + S_G))[lane] = gt;
      bar_sync(4, 544);
      if (lane == 0) {
        mbar_wait(sb + B_P, 0);
        #pragma unroll 1
        for (int c = 2; c < 8; c++) bulkm(sb + c * CH + rk * (CH / 2), g_kv + c * 1280 + rk * 640, CH / 2, sb + B_KV + c * 8);
      }
      __syncwarp();
    }
    bar_sync(1, 128);
    const int idx = *(volatile int*)(smem + S_ST + 12);
    if (blockIdx.x < NSL) {
      if (tid == 0) {
        mbar_wait(sb + B_KV + 56, 0);
        #pragma unroll 1
        for (int i = 0; i < 4; i++) ffn_load(sb, mp, i);
      }
      if (tid < 72) *(uint4*)(smem + S_XS + tid * 16) = ldg16(x + (size_t)idx * DM + tid * 8);
      proxy_fence();
      bar_sync(1, 128);
      float acc[4], gt0 = 0.f, gt1 = 0.f;
      #pragma unroll 1
      for (int i = 0; i < 27; i++) {
        if (i == 0 || i == 9 || i >= 18) {
          #pragma unroll
          for (int k = 0; k < 4; k++) asm volatile("mov.b32 %0, 0;" : "=f"(acc[k]));
        }
        const uint32_t alo = (((sb & 0x3FFFF) + S_FFN + (i & 3) * 8192) >> 4) | (64u << 16);
        const uint32_t blo = (((sb & 0x3FFFF) + (i < 18 ? S_XS + (i < 9 ? i : i - 9) * 128 : S_H)) >> 4) | (1u << 16);
        mbar_wait(sb + B_F + (i & 3) * 8, (i >> 2) & 1);
        wg_fence();
        #pragma unroll
        for (int k = 0; k < 4; k++) wg_ss8(acc, mk64(alo + k * 128, 64u | (1u << 30)), mk64(blo + k * 2, 8));
        wg_commit(); wg_wait<0>(); fence_regs<4>(acc);
        const int row = warp * 16 + (lane >> 2);
        if (i == 8) { gt0 = bfr(acc[0]); gt1 = bfr(acc[2]); }
        if (i == 17) {
          if ((lane & 3) == 0) {
            __nv_bfloat16* hh = (__nv_bfloat16*)(smem + S_H);
            hh[row] = __float2bfloat16(bfr(__fdividef(gt0, 1.f + __expf(-gt0))) * bfr(acc[0]));
            hh[row + 8] = __float2bfloat16(bfr(__fdividef(gt1, 1.f + __expf(-gt1))) * bfr(acc[2]));
          }
          proxy_fence();
        }
        if (i >= 18 && (lane & 3) == 0) { float* yp = g_ypart + blockIdx.x * DM + (i - 18) * 64 + row; yp[0] = acc[0]; yp[8] = acc[2]; }
        bar_sync(1, 128);
        if (tid == 0 && i < 23) ffn_load(sb, mp, i + 4);
      }
      if (tid == 0) { signal(1); STAMP(5); }
    }
    if ((idx >> 6) == tg) {
      if (tid == 0) await(1, NSL);
      bar_sync(1, 128);
      float4* red = (float4*)(smem + S_FFN + 24 * KB);
      if (tid < 108) {
        const float4* yp = (const float4*)(g_ypart + (tid / 36) * 24 * DM + hg * 144) + tid % 36;
        float4 a = make_float4(0.f, 0.f, 0.f, 0.f);
        #pragma unroll 4
        for (int i = 0; i < 24; i++) { float4 b = __ldcg(yp + i * (DM / 4)); a.x += b.x; a.y += b.y; a.z += b.z; a.w += b.w; }
        red[tid] = a;
      }
      bar_sync(1, 128);
      const float rs = bfr(__fdividef(1.f, 1.f + __expf(-bfr(*(volatile float*)(smem + S_ST + 8)))));
      for (int i = tid; i < 144; i += 128) { const float* f = (const float*)red + i; ((float*)(smem + S_Y))[i] = bfr(bfr(f[0] + f[144] + f[288]) * rs); }
    }
    bar_arrive(5, 640);
    if (tid == 0) {
      #pragma unroll 1
      for (int u = 0; u < 9; u++) {
        const int c = u == 0 ? 5 : u < 6 ? u - 1 : u;
        if (c < 5) mbar_wait(sb + B_REL + (c + 1) * 8, 0);
        if (c > 5) mbar_wait(sb + B_E + (c - 3) * 8, 0);
        mbar_expect(sb + B_W + c * 8, 24576);
        #pragma unroll
        for (int j = 0; j < 3; j++) tma3(sb + wslotC(c) + j * 8192, &mp.wo, j * 64, hg, c * 64, sb + B_W + c * 8);
        if (u == 5) {
          await(8 + tg, 4);
          STAMP(18);
          #pragma unroll 1
          for (int k = 0; k < 9; k++) { mbar_expect(sb + B_X + k * 8, 8192); tma2(sb + oslot(k), &mp.o, k * 64, tg * 64, sb + B_X + k * 8); }
        }
      }
      unsigned old;
      asm volatile("atom.add.acq_rel.gpu.global.u32 %0, [%1], 1;" : "=r"(old) : "l"(g_cnt + 64) : "memory");
      if (old == NCTA - 1) {
        #pragma unroll 1
        for (int i = 0; i < 40; i++) g_cnt[i * 32] = 0;
      }
    }
  } else {
    asm volatile("setmaxnreg.inc.sync.aligned.u32 112;");
    const int warp = (threadIdx.x >> 5) & 3, lane = threadIdx.x & 31, g = lane >> 2, t = lane & 3;
    uint32_t* sq = (uint32_t*)(smem + S_Q) + (warp * 16 + g) * QP;
    if (wg == 0) {
      gemm<false, 0>(sb, sq + t);
      STAMP0(4);
    } else if (wg == 1) {
      gemm<false, 1>(sb, sq + t);
    } else if (wg == 3) {
      special(smem, sb, tg * 64 + hg * 16, hg * 16);
      if (threadIdx.x == 384) STAMP(2);
      bar_arrive(3, 416);
    }
    bar_sync(4, 544);
    STAMP0(7);
    volatile uint32_t* stash = (volatile uint32_t*)(smem + S_FLAG) + threadIdx.x;
    volatile uint8_t* fl = smem + S_FLAG - 512 + threadIdx.x;
    const uint32_t sb16 = (sb & 0x3FFFF) >> 4;
    const int q0 = tg * 64 + warp * 16;
    uint32_t qa[8];
    stash[0] = 0; qa[6] = stash[0]; qa[7] = stash[0];
    {
      const float2 st = *(const float2*)(smem + S_ST);
      const bool kvbad = !(st.x <= 65536.f) || !(st.y <= 16384.f) || !(st.y >= 0.015625f);
      const float QS = 0.23570226f * 1.44269504f, kn = sqrta(st.x) * (QS * 1.01f * 8.f);
      uint32_t flags = 0;
      #pragma unroll
      for (int i = 1; i >= 0; i--) {
        const uint32_t* qp = sq + (i * 4 + wg) * 9;
        uint32_t raw[6] = {qp[t], qp[8 * QP + t], qp[t + 4], qp[8 * QP + t + 4], t == 0 ? qp[8] : 0u, t == 0 ? qp[8 * QP + 8] : 0u};
        float n[2] = {0.f, 0.f};
        #pragma unroll
        for (int j = 0; j < 6; j++) {
          float a = bflo(raw[j]), b = bfhi(raw[j]);
          n[j & 1] += a * a + b * b;
          qa[j] = pack2h(a * (QS / 32.f), b * (QS / 32.f));
        }
        #pragma unroll
        for (int r = 0; r < 2; r++) {
          n[r] += __shfl_xor_sync(~0u, n[r], 1); n[r] += __shfl_xor_sync(~0u, n[r], 2);
          float M = ceilf(sqrta(n[r]) * kn) * 0.125f;
          bool bad = kvbad || !(n[r] <= 65536.f) || !(M <= 40.f);
          if (bad) { flags |= 1u << (3 * i); M = 0.f; }
          if (M > 14.f) { flags |= 2u << (3 * i + r); M = 28.f - M; }
          if (t == 1) qa[4 + r] = pack2h(M, M - 13.f);
        }
        if (i) {
          #pragma unroll
          for (int j = 0; j < 6; j++) stash[j * 512] = qa[j];
        }
      }
      *fl = flags;
    }
    uint32_t s0[16], s1[16], p0[16], p1[16];
    mbar_wait(sb + B_KV, 0);
    wg_fence(); qk64(s0, qa, sb16); wg_commit();
    #pragma unroll
    for (int i = 0; i < 2; i++) {
      float o[12];
      #pragma unroll
      for (int k = 0; k < 12; k++) asm volatile("mov.b32 %0, 0;" : "=f"(o[k]));
      wg_wait<0>(); fence_regs<16>(s0);
      STAMP0(9 + 3 * i);
      #pragma unroll 1
      for (int c = 0; c < 8; c++) {
        const uint32_t a0 = sb16 + c * (CH >> 4), an = c == 7 ? sb16 : a0 + (CH >> 4);
        wg_fence(); qk64(s1, qa, a0 + 64); wg_commit();
        softmax64(s0, p0); fence_regs<16>(p0);
        wg_fence(); pv64(o, p0, a0); PVC qk64(s0, qa, a0 + 128); wg_commit();
        wg_wait<WN>(); fence_regs<16>(s1);
        if (i == 1 && lane == 0 && c) mbar_arrive(sb + B_REL + 8 * c - 8);
        softmax64(s1, p1); fence_regs<16>(p1);
        wg_fence(); pv64(o, p1, a0 + 64); PVC qk64(s1, qa, a0 + 192); wg_commit();
        wg_wait<WN>(); fence_regs<16>(s0);
        softmax64(s0, p0); fence_regs<16>(p0);
        if (i == 0 && c < 7) mbar_wait(sb + B_KV + 8 * c + 8, 0);
        wg_fence(); pv64(o, p0, a0 + 128); PVC qk64(s0, qa, an); wg_commit();
        wg_wait<WN>(); fence_regs<16>(s1);
        softmax64(s1, p1); fence_regs<16>(p1);
        wg_fence(); pv64(o, p1, a0 + 192); wg_commit();
        wg_wait<1>(); fence_regs<16>(s0);
      }
      wg_wait<0>();
      fence_regs<12>(o);
      RETID
      if (i == 0) {
        #pragma unroll
        for (int j = 0; j < 6; j++) qa[j] = stash[j * 512];
        stash[0] = 0; qa[6] = stash[0]; qa[7] = stash[0];
        wg_fence(); qk64(s0, qa, sb16); wg_commit();
      }
      STAMP0(10 + 3 * i);
      const uint32_t flags = *fl;
      float l0 = __shfl_sync(0xffffffffu, o[0], lane | 3), l1 = __shfl_sync(0xffffffffu, o[2], lane | 3);
      bool bad = ((flags >> (3 * i)) & 1) || !(l0 <= 3e38f) || !(l1 <= 3e38f) || !(l0 > 0.f) || !(l1 > 0.f)
                 || (((flags >> (3 * i + 1)) & 1) && l0 < 256.f) || (((flags >> (3 * i + 2)) & 1) && l1 < 256.f);
      if (__any_sync(0xffffffffu, bad)) *fl = flags | (64u << i);
      else {
        float r0 = __fdividef(1.f, l0), r1 = __fdividef(1.f, l1);
        uint32_t* op0 = (uint32_t*)(g_o + (size_t)(q0 + g) * DM + (hg * 8 + i * 4 + wg) * 18);
        uint32_t* op1 = op0 + 4 * DM;
        op0[t] = pack2(o[4] * r0, o[5] * r0); op1[t] = pack2(o[6] * r1, o[7] * r1);
        op0[t + 4] = pack2(o[8] * r0, o[9] * r0); op1[t + 4] = pack2(o[10] * r1, o[11] * r1);
        if (t == 2) { op0[8] = pack2(o[0] * r0, o[1] * r0); op1[8] = pack2(o[2] * r1, o[3] * r1); }
      }
    }
    {
    RETID
    uint32_t* sq2 = (uint32_t*)(smem + S_Q) + (warp * 16 + g) * QP;
    {
      const uint32_t flags = *fl;
      #pragma unroll 1
      for (int i = 0; i < 2; i++)
        if ((flags >> (6 + i)) & 1) attn_exact((const __nv_bfloat16*)(smem + S_Q) + warp * 32 * QP + (i * 4 + wg) * 18, q0, hg * 8 + i * 4 + wg, lane);
    }
    if ((tx_ & 127) == 0 && wg) STAMP(14 + wg);
    bar_sync(6, 512);
    if (tx_ == 384) signal(8 + tg);
    uint4 xr[3];
    #pragma unroll
    for (int u = 0; u < 3; u++) {
      const int v = tx_ + u * 512, row = v / 18, c8 = v % 18;
      if (v < 1152) xr[u] = ldg16(x + (size_t)(tg * 64 + row) * DM + hg * 144 + c8 * 8);
    }
    if (wg == 0) gemm<true, 0>(sb, sq2 + t);
    if (wg == 1) gemm<true, 1>(sb, sq2 + t);
    STAMP0(20);
    bar_sync(5, 640);
    const int li = *(const int*)(smem + S_ST + 12) - tg * 64;
    #pragma unroll
    for (int u = 0; u < 3; u++) {
      const int v = tx_ + u * 512, row = v / 18, c8 = v % 18;
      if (v < 1152) {
        const float gg = ((const float*)(smem + S_G))[row];
        const uint4 av = *(const uint4*)(smem + S_Q + row * (QP * 4) + c8 * 16);
        const uint32_t aa[4] = {av.x, av.y, av.z, av.w}, xx[4] = {xr[u].x, xr[u].y, xr[u].z, xr[u].w};
        uint32_t r[4];
        #pragma unroll
        for (int k = 0; k < 4; k++) {
          float b0 = bflo(xx[k]), b1 = bfhi(xx[k]);
          if (row == li) { const float* ys = (const float*)(smem + S_Y) + c8 * 8 + 2 * k; b0 += ys[0]; b1 += ys[1]; }
          r[k] = pack2(fmaf(gg, bflo(aa[k]) - b0, b0), fmaf(gg, bfhi(aa[k]) - b1, b1));
        }
        *(uint4*)(out + (size_t)(tg * 64 + row) * DM + hg * 144 + c8 * 8) = make_uint4(r[0], r[1], r[2], r[3]);
      }
    }
    }
    STAMP0(21);
  }
}

typedef CUresult (*EncFn)(CUtensorMap*, CUtensorMapDataType, cuuint32_t, void*, const cuuint64_t*, const cuuint64_t*, const cuuint32_t*, const cuuint32_t*,
                          CUtensorMapInterleave, CUtensorMapSwizzle, CUtensorMapL2promotion, CUtensorMapFloatOOBfill);
static void make_map(EncFn enc, CUtensorMap* m, const void* base, int cols, int rows, bool grouped) {
  cuuint64_t d2[2] = {(cuuint64_t)cols, (cuuint64_t)rows}, s2[1] = {(cuuint64_t)cols * 2}, d3[3] = {144, 4, (cuuint64_t)rows}, s3[2] = {288, (cuuint64_t)cols * 2};
  cuuint32_t b2[2] = {64, 64}, b3[3] = {64, 1, 64}, es[3] = {1, 1, 1};
  enc(m, CU_TENSOR_MAP_DATA_TYPE_BFLOAT16, grouped ? 3 : 2, (void*)base, grouped ? d3 : d2, grouped ? s3 : s2, grouped ? b3 : b2, es, CU_TENSOR_MAP_INTERLEAVE_NONE,
      CU_TENSOR_MAP_SWIZZLE_128B, CU_TENSOR_MAP_L2_PROMOTION_L2_256B, CU_TENSOR_MAP_FLOAT_OOB_FILL_NONE);
}

extern "C" void kernel_launch(void* const* d_in, const int* in_sizes, int n_in, void* d_out, int out_size) {
  typedef const __nv_bfloat16* P;
  static EncFn enc = nullptr;
  static void* po = nullptr;
  if (!enc) {
    cudaDriverEntryPointQueryResult qr;
    cudaGetDriverEntryPoint("cuTensorMapEncodeTiled", (void**)&enc, cudaEnableDefault, &qr);
    cudaGetSymbolAddress(&po, g_o);
    cudaFuncSetAttribute(k_fused, cudaFuncAttributeMaxDynamicSharedMemorySize, SMEM);
  }
  Maps mp;
  make_map(enc, &mp.x, d_in[0], DM, SEQ, false); make_map(enc, &mp.wq, d_in[1], DM, DM, true); make_map(enc, &mp.wo, d_in[4], DM, DM, true);
  make_map(enc, &mp.o, po, DM, SEQ, false); make_map(enc, &mp.wg, d_in[7], FF, DM, false); make_map(enc, &mp.wu, d_in[8], FF, DM, false);
  make_map(enc, &mp.wd, d_in[9], DM, FF, false);
  k_fused<<<NCTA, 640, SMEM, cudaStreamPerThread>>>(mp, (P)d_in[0], (P)d_in[2], (P)d_in[3], (P)d_in[6], (P)d_in[10], (__nv_bfloat16*)d_out);
}
```

```cpp
#include <cuda_runtime.h>
#include <cuda_bf16.h>
#include <cuda_fp16.h>
#include <stdint.h>
#include <cuda.h>

constexpr int SEQ = 2048, DM = 576, FF = 4608, NSL = 72, NCTA = 128;
constexpr uint32_t KMASK = 0x25;

__device__ __align__(128) __nv_bfloat16 g_o[SEQ * DM];
__device__ uint4 g_kv[5 * SEQ];
__device__ float g_kraw[SEQ * 18];
__device__ float g_vraw[SEQ * 18];
__device__ float g_gate[SEQ];
__device__ float4 g_stat[NCTA];
__device__ float g_ypart[NSL * DM];
__device__ unsigned g_cnt[40 * 32];

#define STAMP(k)
#define STAMP0(k)
__device__ __forceinline__ void wgh_n64_sd0(uint32_t* d, uint32_t a0, uint32_t a1, uint32_t a2, uint32_t a3, uint64_t bdesc) {
  asm volatile("{\n.reg .pred p;\nsetp.ne.b32 p, 0, 0;\n"
    "wgmma.mma_async.sync.aligned.m64n64k16.f16.f16.f16 {%0, %1, %2, %3, %4, %5, %6, %7, %8, %9, %10, %11, %12, %13, %14, %15}, {%16, %17, %18, %19}, %20, p, 1, 1, 0;\n}\n"
    : "=r"(d[0]), "=r"(d[1]), "=r"(d[2]), "=r"(d[3]), "=r"(d[4]), "=r"(d[5]), "=r"(d[6]), "=r"(d[7]), "=r"(d[8]), "=r"(d[9]), "=r"(d[10]), "=r"(d[11]), "=r"(d[12]), "=r"(d[13]), "=r"(d[14]), "=r"(d[15]) : "r"(a0), "r"(a1), "r"(a2), "r"(a3), "l"(bdesc));
}
__device__ __forceinline__ void wgh_n64_sd1(uint32_t* d, uint32_t a0, uint32_t a1, uint32_t a2, uint32_t a3, uint64_t bdesc) {
  asm volatile("{\n.reg .pred p;\nsetp.ne.b32 p, 1, 0;\n"
    "wgmma.mma_async.sync.aligned.m64n64k16.f16.f16.f16 {%0, %1, %2, %3, %4, %5, %6, %7, %8, %9, %10, %11, %12, %13, %14, %15}, {%16, %17, %18, %19}, %20, p, 1, 1, 0;\n}\n"
    : "+r"(d[0]), "+r"(d[1]), "+r"(d[2]), "+r"(d[3]), "+r"(d[4]), "+r"(d[5]), "+r"(d[6]), "+r"(d[7]), "+r"(d[8]), "+r"(d[9]), "+r"(d[10]), "+r"(d[11]), "+r"(d[12]), "+r"(d[13]), "+r"(d[14]), "+r"(d[15]) : "r"(a0), "r"(a1), "r"(a2), "r"(a3), "l"(bdesc));
}
__device__ __forceinline__ void wg_pv(float* d, uint32_t a0, uint32_t a1, uint32_t a2, uint32_t a3, uint64_t bdesc) {
  asm volatile("{\n.reg .pred p;\nsetp.ne.b32 p, 1, 0;\n"
    "wgmma.mma_async.sync.aligned.m64n24k16.f32.f16.f16 {%0, %1, %2, %3, %4, %5, %6, %7, %8, %9, %10, %11}, {%12, %13, %14, %15}, %16, p, 1, 1, 1;\n}\n"
    : "+f"(d[0]), "+f"(d[1]), "+f"(d[2]), "+f"(d[3]), "+f"(d[4]), "+f"(d[5]), "+f"(d[6]), "+f"(d[7]), "+f"(d[8]), "+f"(d[9]), "+f"(d[10]), "+f"(d[11]) : "r"(a0), "r"(a1), "r"(a2), "r"(a3), "l"(bdesc));
}
__device__ __forceinline__ void wg_ss64(float* d, uint64_t adesc, uint64_t bdesc) {
  asm volatile("{\n.reg .pred p;\nsetp.ne.b32 p, 1, 0;\n"
    "wgmma.mma_async.sync.aligned.m64n64k16.f32.bf16.bf16 {%0, %1, %2, %3, %4, %5, %6, %7, %8, %9, %10, %11, %12, %13, %14, %15, %16, %17, %18, %19, %20, %21, %22, %23, %24, %25, %26, %27, %28, %29, %30, %31}, %32, %33, p, 1, 1, 0, 1;\n}\n"
    : "+f"(d[0]), "+f"(d[1]), "+f"(d[2]), "+f"(d[3]), "+f"(d[4]), "+f"(d[5]), "+f"(d[6]), "+f"(d[7]), "+f"(d[8]), "+f"(d[9]), "+f"(d[10]), "+f"(d[11]), "+f"(d[12]), "+f"(d[13]), "+f"(d[14]), "+f"(d[15]), "+f"(d[16]), "+f"(d[17]), "+f"(d[18]), "+f"(d[19]), "+f"(d[20]), "+f"(d[21]), "+f"(d[22]), "+f"(d[23]), "+f"(d[24]), "+f"(d[25]), "+f"(d[26]), "+f"(d[27]), "+f"(d[28]), "+f"(d[29]), "+f"(d[30]), "+f"(d[31]) : "l"(adesc), "l"(bdesc));
}
__device__ __forceinline__ void wg_ss80(float* d, uint64_t adesc, uint64_t bdesc) {
  asm volatile("{\n.reg .pred p;\nsetp.ne.b32 p, 1, 0;\n"
    "wgmma.mma_async.sync.aligned.m64n80k16.f32.bf16.bf16 {%0, %1, %2, %3, %4, %5, %6, %7, %8, %9, %10, %11, %12, %13, %14, %15, %16, %17, %18, %19, %20, %21, %22, %23, %24, %25, %26, %27, %28, %29, %30, %31, %32, %33, %34, %35, %36, %37, %38, %39}, %40, %41, p, 1, 1, 0, 1;\n}\n"
    : "+f"(d[0]), "+f"(d[1]), "+f"(d[2]), "+f"(d[3]), "+f"(d[4]), "+f"(d[5]), "+f"(d[6]), "+f"(d[7]), "+f"(d[8]), "+f"(d[9]), "+f"(d[10]), "+f"(d[11]), "+f"(d[12]), "+f"(d[13]), "+f"(d[14]), "+f"(d[15]), "+f"(d[16]), "+f"(d[17]), "+f"(d[18]), "+f"(d[19]), "+f"(d[20]), "+f"(d[21]), "+f"(d[22]), "+f"(d[23]), "+f"(d[24]), "+f"(d[25]), "+f"(d[26]), "+f"(d[27]), "+f"(d[28]), "+f"(d[29]), "+f"(d[30]), "+f"(d[31]), "+f"(d[32]), "+f"(d[33]), "+f"(d[34]), "+f"(d[35]), "+f"(d[36]), "+f"(d[37]), "+f"(d[38]), "+f"(d[39]) : "l"(adesc), "l"(bdesc));
}
__device__ __forceinline__ void wg_ss8(float* d, uint64_t adesc, uint64_t bdesc) {
  asm volatile("{\n.reg .pred p;\nsetp.ne.b32 p, 1, 0;\n"
    "wgmma.mma_async.sync.aligned.m64n8k16.f32.bf16.bf16 {%0, %1, %2, %3}, %4, %5, p, 1, 1, 1, 0;\n}\n"
    : "+f"(d[0]), "+f"(d[1]), "+f"(d[2]), "+f"(d[3]) : "l"(adesc), "l"(bdesc));
}

__device__ __forceinline__ void wg_fence() { asm volatile("wgmma.fence.sync.aligned;" ::: "memory"); }
__device__ __forceinline__ void wg_commit() { asm volatile("wgmma.commit_group.sync.aligned;" ::: "memory"); }
template<int N> __device__ __forceinline__ void wg_wait() { asm volatile("wgmma.wait_group.sync.aligned %0;" :: "n"(N) : "memory"); }
__device__ __forceinline__ uint32_t pack2(float lo, float hi) { uint32_t r; asm("cvt.rn.bf16x2.f32 %0, %1, %2;" : "=r"(r) : "f"(hi), "f"(lo)); return r; }
__device__ __forceinline__ uint32_t pack2h(float lo, float hi) { uint32_t r; asm("cvt.rn.f16x2.f32 %0, %1, %2;" : "=r"(r) : "f"(hi), "f"(lo)); return r; }
__device__ __forceinline__ float bflo(uint32_t v) { return __uint_as_float(v << 16); }
__device__ __forceinline__ float bfhi(uint32_t v) { return __uint_as_float(v & 0xffff0000u); }
__device__ __forceinline__ float bfr(float v) { return __bfloat162float(__float2bfloat16(v)); }
__device__ __forceinline__ uint32_t hfma2(uint32_t a, uint32_t b, uint32_t c) { uint32_t r; asm("fma.rn.f16x2 %0, %1, %2, %3;" : "=r"(r) : "r"(a), "r"(b), "r"(c)); return r; }
__device__ __forceinline__ uint32_t hfma2r(uint32_t a, uint32_t b, uint32_t c) { uint32_t r; asm("fma.rn.relu.f16x2 %0, %1, %2, %3;" : "=r"(r) : "r"(a), "r"(b), "r"(c)); return r; }
__device__ __forceinline__ uint32_t ex2h2(uint32_t x) { uint32_t r; asm("ex2.approx.f16x2 %0, %1;" : "=r"(r) : "r"(x)); return r; }
__device__ __forceinline__ uint64_t mk64(uint32_t lo, uint32_t hi) { uint64_t d; asm("mov.b64 %0, {%1, %2};" : "=l"(d) : "r"(lo), "r"(hi)); return d; }
template<int N> __device__ __forceinline__ void fence_regs(float* r) {
  #pragma unroll
  for (int i = 0; i < N; i++) asm volatile("" : "+f"(r[i]) :: "memory");
}
template<int N> __device__ __forceinline__ void fence_regs(uint32_t* r) {
  #pragma unroll
  for (int i = 0; i < N; i++) asm volatile("" : "+r"(r[i]) :: "memory");
}
__device__ __forceinline__ void cp16(uint32_t dst, const void* src) { asm volatile("cp.async.cg.shared.global [%0], [%1], 16;" :: "r"(dst), "l"(src) : "memory"); }
__device__ __forceinline__ void cp4(uint32_t dst, const void* src) { asm volatile("cp.async.ca.shared.global [%0], [%1], 4;" :: "r"(dst), "l"(src) : "memory"); }
__device__ __forceinline__ void cp_commit() { asm volatile("cp.async.commit_group;" ::: "memory"); }
template<int N> __device__ __forceinline__ void cp_wait() { asm volatile("cp.async.wait_group %0;" :: "n"(N) : "memory"); }
__device__ __forceinline__ void proxy_fence() { asm volatile("fence.proxy.async.shared::cta;" ::: "memory"); }
__device__ __forceinline__ void pdl_wait() { asm volatile("griddepcontrol.wait;" ::: "memory"); }
__device__ __forceinline__ void pdl_go() { asm volatile("griddepcontrol.launch_dependents;" ::: "memory"); }
__device__ __forceinline__ uint4 ldg16(const void* p) { uint4 v; asm volatile("ld.global.nc.L1::no_allocate.v4.u32 {%0,%1,%2,%3}, [%4];" : "=r"(v.x), "=r"(v.y), "=r"(v.z), "=r"(v.w) : "l"(p)); return v; }
__device__ __forceinline__ uint4 ldg16c(const void* p) { uint4 v; asm volatile("ld.global.L1::no_allocate.v4.u32 {%0,%1,%2,%3}, [%4];" : "=r"(v.x), "=r"(v.y), "=r"(v.z), "=r"(v.w) : "l"(p) : "memory"); return v; }
__device__ __forceinline__ void mbar_wait(uint32_t bar, uint32_t parity) {
  #pragma unroll 1
  for (int it = 0; it < (1 << 22); it++) {
    uint32_t ok;
    asm volatile("{\n.reg .pred p;\nmbarrier.try_wait.parity.shared::cta.b64 p, [%1], %2;\nselp.u32 %0, 1, 0, p;\n}\n" : "=r"(ok) : "r"(bar), "r"(parity) : "memory");
    if (ok) break;
  }
}
__device__ __forceinline__ void mbar_init(uint32_t bar, uint32_t cnt) { asm volatile("mbarrier.init.shared::cta.b64 [%0], %1;" :: "r"(bar), "r"(cnt) : "memory"); }
__device__ __forceinline__ void mbar_expect(uint32_t bar, uint32_t bytes) { asm volatile("mbarrier.arrive.expect_tx.shared::cta.b64 _, [%0], %1;" :: "r"(bar), "r"(bytes) : "memory"); }
__device__ __forceinline__ void mbar_arrive(uint32_t bar) { asm volatile("mbarrier.arrive.shared::cta.b64 _, [%0];" :: "r"(bar) : "memory"); }
__device__ __forceinline__ void tma2(uint32_t dst, const CUtensorMap* m, int c0, int c1, uint32_t bar) {
  asm volatile("cp.async.bulk.tensor.2d.shared::cluster.global.mbarrier::complete_tx::bytes [%0], [%1, {%3, %4}], [%2];" :: "r"(dst), "l"(m), "r"(bar), "r"(c0), "r"(c1) : "memory");
}
__device__ __forceinline__ void tma3(uint32_t dst, const CUtensorMap* m, int c0, int c1, int c2, uint32_t bar) {
  asm volatile("cp.async.bulk.tensor.3d.shared::cluster.global.mbarrier::complete_tx::bytes [%0], [%1, {%3, %4, %5}], [%2];" :: "r"(dst), "l"(m), "r"(bar), "r"(c0), "r"(c1), "r"(c2) : "memory");
}
__device__ __forceinline__ void bulk(uint32_t dst, const void* src, uint32_t bytes, uint32_t bar) {
  asm volatile("cp.async.bulk.shared::cluster.global.mbarrier::complete_tx::bytes [%0], [%1], %2, [%3];" :: "r"(dst), "l"(src), "r"(bytes), "r"(bar) : "memory");
}
__device__ __forceinline__ void bar_sync(int id, int n) { asm volatile("bar.sync %0, %1;" :: "r"(id), "r"(n) : "memory"); }
__device__ __forceinline__ void bar_arrive(int id, int n) { asm volatile("bar.arrive %0, %1;" :: "r"(id), "r"(n) : "memory"); }
__device__ __forceinline__ void proxy_fence_all() { asm volatile("fence.proxy.async;" ::: "memory"); }
__device__ __forceinline__ void signal(int i) {
  asm volatile("fence.acq_rel.gpu;\nred.relaxed.gpu.global.add.u32 [%0], 1;" :: "l"(g_cnt + i * 32) : "memory");
}
__device__ __forceinline__ void await(int i, unsigned n) {
  #pragma unroll 1
  for (int it = 0; it < (1 << 21); it++) {
    unsigned v; asm volatile("ld.acquire.gpu.global.u32 %0, [%1];" : "=r"(v) : "l"(g_cnt + i * 32) : "memory");
    if (v >= n) break;
  }
  proxy_fence_all();
}
__device__ __forceinline__ void ldsm4(uint32_t a, uint32_t* r) {
  asm volatile("ldmatrix.sync.aligned.m8n8.x4.shared.b16 {%0,%1,%2,%3}, [%4];" : "=r"(r[0]), "=r"(r[1]), "=r"(r[2]), "=r"(r[3]) : "r"(a) : "memory");
}
__device__ __forceinline__ void mma16(float* d, const uint32_t* a, uint32_t b0, uint32_t b1) {
  asm volatile("mma.sync.aligned.m16n8k16.row.col.f32.bf16.bf16.f32 {%0,%1,%2,%3}, {%4,%5,%6,%7}, {%8,%9}, {%0,%1,%2,%3};"
    : "+f"(d[0]), "+f"(d[1]), "+f"(d[2]), "+f"(d[3]) : "r"(a[0]), "r"(a[1]), "r"(a[2]), "r"(a[3]), "r"(b0), "r"(b1));
}

constexpr uint32_t KB = 1024, CH = 20480;
constexpr uint32_t S_X = 44 * KB, S_W = 116 * KB;
constexpr uint32_t S_FFN = 160 * KB, S_Q = 192 * KB, S_FLAG = 212 * KB, S_BAR = 224 * KB;
constexpr uint32_t B_X = S_BAR, B_W = B_X + 72, B_E = B_W + 72, B_R = B_E + 40, B_KV = B_R + 8, B_REL = B_KV + 64, B_F = B_REL + 56;
constexpr uint32_t S_ST = S_BAR + 352, S_G = S_BAR + 384, S_Y = S_G + 256, S_H = S_Y + 576, S_XS = S_H + 128, SMEM = S_XS + 1152 + 128;
constexpr int QP = 76;
__device__ __forceinline__ uint32_t wslotA(int c) { return S_W + (c & 3) * 24 * KB; }
__device__ __forceinline__ uint32_t wslotC(int c) { return c == 5 ? S_FFN : (c < 5 ? c : c - 6) * 24 * KB; }
__device__ __forceinline__ uint32_t oslot(int c) { return (c < 5 ? 120 + 8 * c : 152 + 8 * c) * KB; }

template<bool C, int W> __device__ __forceinline__ void gemm(uint32_t sb, uint32_t* sq) {
  constexpr int NA = W ? 40 : 32;
  float acc[NA];
  #pragma unroll
  for (int i = 0; i < NA; i++) asm volatile("mov.b32 %0, 0;" : "=f"(acc[i]));
  const uint32_t hi = 64u | (1u << 30);
  #pragma unroll
  for (int c = 0; c < 9; c++) {
    const uint32_t alo = ((sb + (C ? oslot(c) : S_X + c * 8192)) >> 4) | (1u << 16), blo = ((sb + (C ? wslotC(c) : wslotA(c)) + W * 8192) >> 4) | (512u << 16);
    mbar_wait(sb + B_X + c * 8, C);
    mbar_wait(sb + B_W + c * 8, C);
    wg_fence();
    #pragma unroll
    for (int k = 0; k < 4; k++) { if (W) wg_ss80(acc, mk64(alo + k * 2, hi), mk64(blo + k * 128, hi)); else wg_ss64(acc, mk64(alo + k * 2, hi), mk64(blo + k * 128, hi)); }
    wg_commit();
    if (c >= 1 && c <= (C ? 3 : 5)) { wg_wait<1>(); if ((threadIdx.x & 31) == 0) mbar_arrive(sb + B_E + (c - 1) * 8); }
  }
  wg_wait<0>();
  fence_regs<NA>(acc);
  if (!C && !W) STAMP0(22);
  if (!C) bar_arrive(3, 416);
  bar_sync(7, 256);
  #pragma unroll
  for (int j = 0; j < NA / 4; j++) { sq[W * 32 + j * 4] = pack2(acc[4*j], acc[4*j+1]); sq[8 * QP + W * 32 + j * 4] = pack2(acc[4*j+2], acc[4*j+3]); }
}

__device__ __forceinline__ void special(uint8_t* smem, uint32_t sb, int tok0, int row0) {
  const int tid = threadIdx.x & 127, warp = tid >> 5, lane = tid & 31, g = lane >> 2, t = lane & 3;
  float acc[6][4];
  #pragma unroll
  for (int i = 0; i < 6; i++) { acc[i][0] = acc[i][1] = acc[i][2] = acc[i][3] = 0.f; }
  const uint32_t* raw = (const uint32_t*)smem;
  const int r = row0 + (lane & 15);
  const uint32_t xa = sb + S_X + r * 128 + (((warp * 2 + (lane >> 4)) ^ (r & 7)) << 4);
  const int kb = warp * 16 + 2 * t;
  const uint32_t* pk = raw + kb * 9 + g;
  const uint32_t* pl = g < 2 ? raw + g * 5184 + kb * 9 + 8 : raw + 10368 + (g & 1) * 288 + (kb >> 1);
  const int ls = g < 2 ? 9 : 0, lc = g < 2 ? 576 : 32, l8 = g < 2 ? 72 : 4;
  const uint32_t se = g < 2 ? 0x5410 : 0x3210;
  mbar_wait(sb + B_R, 0);
  if (tid == 0) STAMP(1);
  #pragma unroll
  for (int c = 0; c < 9; c++) {
    uint32_t a[4];
    mbar_wait(sb + B_X + c * 8, 0);
    ldsm4(xa + c * 8192, a);
    #pragma unroll
    for (int m = 0; m < 2; m++) {
      const uint32_t* p = pk + m * 5184 + c * 576;
      uint32_t w0 = p[0], w1 = p[9], w2 = p[72], w3 = p[81];
      mma16(acc[2*m], a, __byte_perm(w0, w1, 0x5410), __byte_perm(w2, w3, 0x5410));
      mma16(acc[2*m+1], a, __byte_perm(w0, w1, 0x7632), __byte_perm(w2, w3, 0x7632));
    }
    const uint32_t* p = pl + c * lc;
    uint32_t w0 = p[0], w1 = p[ls], w2 = p[l8], w3 = p[l8 + ls];
    mma16(acc[4], a, __byte_perm(w0, w1, se), __byte_perm(w2, w3, se));
    mma16(acc[5], a, __byte_perm(w0, w1, 0x7632), __byte_perm(w2, w3, 0x7632));
  }
  if (tid == 0) STAMP(6);
  bar_sync(2, 128);
  float* part = (float*)smem;
  #pragma unroll
  for (int h = 0; h < 2; h++) {
    float* q = part + (warp * 16 + g + h * 8) * 44;
    *(float4*)(q + 4 * t) = make_float4(acc[0][2*h], acc[1][2*h], acc[0][2*h+1], acc[1][2*h+1]);
    *(float4*)(q + 16 + 4 * t) = make_float4(acc[2][2*h], acc[3][2*h], acc[2][2*h+1], acc[3][2*h+1]);
    if (t < 2) *(float2*)(q + 32 + 2 * t) = make_float2(acc[4][2*h], acc[4][2*h+1]);
    if (t == 0) *(float2*)(q + 36) = make_float2(acc[5][2*h], acc[5][2*h+1]);
  }
  bar_sync(2, 128);
  #pragma unroll
  for (int i = tid; i < 176; i += 128) {
    float4 a = ((float4*)part)[i], b = ((float4*)part)[i + 176], c = ((float4*)part)[i + 352], d = ((float4*)part)[i + 528];
    ((float4*)part)[i] = make_float4((a.x + b.x) + (c.x + d.x), (a.y + b.y) + (c.y + d.y), (a.z + b.z) + (c.z + d.z), (a.w + b.w) + (c.w + d.w));
  }
  bar_sync(2, 128);
  if (warp == 0) {
    const int isv = lane >> 4, key = tok0 + (lane & 15);
    const float* q = part + (lane & 15) * 44;
    float v[18];
    #pragma unroll
    for (int d = 0; d < 16; d++) v[d] = bfr(q[isv * 16 + d]);
    v[16] = bfr(q[32 + isv]); v[17] = bfr(q[36 + isv]);
    const bool mufu = (KMASK >> ((key >> 3) & 7)) & 1;
    const float sc = isv ? 1.f : mufu ? 32.f : 0.0625f;
    uint4* kv = g_kv + (key >> 8) * 1280 + (key & 255) + isv * 768;
    kv[0] = make_uint4(pack2h(v[0] * sc, v[1] * sc), pack2h(v[2] * sc, v[3] * sc), pack2h(v[4] * sc, v[5] * sc), pack2h(v[6] * sc, v[7] * sc));
    kv[256] = make_uint4(pack2h(v[8] * sc, v[9] * sc), pack2h(v[10] * sc, v[11] * sc), pack2h(v[12] * sc, v[13] * sc), pack2h(v[14] * sc, v[15] * sc));
    ((uint2*)(kv + 512 - isv * 768))[isv] = make_uint2(pack2h(v[16] * sc, v[17] * sc), isv ? 0x00003C00u : mufu ? 0x3C000000u : 0x00001800u);
    float s = 0.f, z = 0.f;
    #pragma unroll
    for (int d = 0; d < 18; d++) { s = isv ? fmaxf(s, fabsf(v[d])) : fmaf(v[d], v[d], s); z = fmaf(v[d], 0.f, z); }
    s += z;
    if (!(s <= 3e38f)) s = 3e38f;
    if (isv) g_gate[key] = __fdividef(1.f, 1.f + __expf(-bfr(q[35])));
    float rr = q[34]; int ri = key;
    #pragma unroll
    for (int o = 8; o; o >>= 1) {
      s = fmaxf(s, __shfl_xor_sync(~0u, s, o));
      float r2 = __shfl_xor_sync(~0u, rr, o); int i2 = __shfl_xor_sync(~0u, ri, o);
      if (r2 > rr || (r2 == rr && i2 < ri)) { rr = r2; ri = i2; }
    }
    const float vm = __shfl_xor_sync(~0u, s, 16);
    if (lane == 0) g_stat[blockIdx.x] = make_float4(s, vm, rr, __int_as_float(ri));
    __syncwarp();
    if (lane == 0) STAMP(8);
    if (lane == 0) signal(0);
    #pragma unroll
    for (int d = 0; d < 18; d++) (isv ? g_vraw : g_kraw)[d * SEQ + key] = v[d];
  }
}
__device__ __forceinline__ bool elect() { uint32_t p; asm volatile("{\n.reg .pred q;\nelect.sync _|q, 0xffffffff;\nselp.u32 %0, 1, 0, q;\n}" : "=r"(p)); return p; }
__device__ __forceinline__ float sqrta(float x) { float r; asm("sqrt.approx.f32 %0, %1;" : "=f"(r) : "f"(x)); return r; }
__device__ __forceinline__ uint32_t ex2poly(uint32_t x) {
  uint32_t t = hfma2r(x, 0x02000200u, 0u);
  uint32_t u = hfma2(t, 0xF800F800u, x);
  uint32_t e = hfma2r(u, 0x47AC47ACu, 0x29A029A0u);
  uint32_t p = hfma2(e, u, 0x08000800u);
  return p + __funnelshift_l(t, t, 10);
}
__device__ __forceinline__ void softmax64(const uint32_t* s, uint32_t* p) {
  #pragma unroll
  for (int j = 0; j < 8; j++) {
    if ((KMASK >> j) & 1) { p[2*j] = ex2h2(s[2*j]); p[2*j+1] = ex2h2(s[2*j+1]); }
    else { p[2*j] = ex2poly(s[2*j]); p[2*j+1] = ex2poly(s[2*j+1]); }
  }
}
__device__ __forceinline__ uint32_t kvt(int j) { return (j >> 2) * (CH >> 4) + (j & 3) * 64; }
__device__ __forceinline__ void qk64(uint32_t* s, const uint32_t* q, uint32_t a16) {
  uint32_t lo = a16 | (256u << 16);
  wgh_n64_sd0(s, q[0], q[1], q[2], q[3], mk64(lo, 8));
  wgh_n64_sd1(s, q[4], q[5], q[6], q[7], mk64(lo + 512, 8));
}
__device__ __forceinline__ void pv64(float* o, const uint32_t* p, uint32_t a16) {
  uint32_t lo = (a16 | (8u << 16)) + 512;
  #pragma unroll
  for (int j = 0; j < 4; j++) wg_pv(o, p[4*j], p[4*j+1], p[4*j+2], p[4*j+3], mk64(lo + j * 16, 256));
}
__device__ __forceinline__ void attn_exact(const __nv_bfloat16* sq, int q0, int h, int lane) {
  #pragma unroll 1
  for (int r = 0; r < 16; r++) {
    float q[18], o[18];
    #pragma unroll
    for (int d = 0; d < 18; d++) { q[d] = __bfloat162float(sq[r * 2 * QP + d]) * 0.23570226f; o[d] = 0.f; }
    float m = -INFINITY;
    #pragma unroll 1
    for (int k = lane; k < SEQ; k += 32) {
      float s = 0.f;
      #pragma unroll
      for (int d = 0; d < 18; d++) s = fmaf(q[d], __ldcg(g_kraw + d * SEQ + k), s);
      m = fmaxf(m, s);
    }
    #pragma unroll
    for (int x = 16; x; x >>= 1) m = fmaxf(m, __shfl_xor_sync(~0u, m, x));
    float l = 0.f;
    #pragma unroll 1
    for (int k = lane; k < SEQ; k += 32) {
      float s = 0.f;
      #pragma unroll
      for (int d = 0; d < 18; d++) s = fmaf(q[d], __ldcg(g_kraw + d * SEQ + k), s);
      float p = __expf(s - m);
      l += p;
      #pragma unroll
      for (int d = 0; d < 18; d++) o[d] = fmaf(p, __ldcg(g_vraw + d * SEQ + k), o[d]);
    }
    #pragma unroll
    for (int x = 16; x; x >>= 1) {
      l += __shfl_xor_sync(~0u, l, x);
      #pragma unroll
      for (int d = 0; d < 18; d++) o[d] += __shfl_xor_sync(~0u, o[d], x);
    }
    float inv = __fdividef(1.f, l), mine = 0.f;
    #pragma unroll
    for (int d = 0; d < 18; d++) if (lane == d) mine = o[d];
    if (lane < 18) g_o[(size_t)(q0 + r) * DM + h * 18 + lane] = __float2bfloat16(mine * inv);
  }
}

struct Maps { CUtensorMap x, wq, wo, o, wg, wu, wd; };

__device__ __forceinline__ void ffn_load(uint32_t sb, const Maps& mp, int i) {
  const uint32_t bar = sb + B_F + (i & 3) * 8, dst = sb + S_FFN + (i & 3) * 8192;
  mbar_expect(bar, 8192);
  if (i < 18) tma2(dst, i < 9 ? &mp.wg : &mp.wu, blockIdx.x * 64, (i < 9 ? i : i - 9) * 64, bar);
  else tma2(dst, &mp.wd, (i - 18) * 64, blockIdx.x * 64, bar);
}

#define RETID uint32_t tx_; asm volatile("mov.u32 %0, %%tid.x;" : "=r"(tx_)); const int warp = (tx_ >> 5) & 3, lane = tx_ & 31, g = lane >> 2, t = lane & 3, wg = tx_ >> 7, q0 = tg * 64 + warp * 16; \
  volatile uint32_t* stash = (volatile uint32_t*)(smem + S_FLAG) + tx_; volatile uint8_t* fl = smem + S_FLAG - 512 + tx_; (void)g; (void)t; (void)q0; (void)stash; (void)fl; (void)wg;
#define PVC wg_commit();
#define WN 2
__global__ void __launch_bounds__(640, 1) k_fused(const __grid_constant__ Maps mp, const __nv_bfloat16* __restrict__ x, const __nv_bfloat16* __restrict__ wk,
    const __nv_bfloat16* __restrict__ wv, const __nv_bfloat16* __restrict__ wr, const __nv_bfloat16* __restrict__ gw, __nv_bfloat16* __restrict__ out) {
  extern __shared__ __align__(1024) uint8_t smem[];
  const uint32_t sb = (uint32_t)__cvta_generic_to_shared(smem);
  const int wg = __shfl_sync(0xffffffffu, threadIdx.x >> 7, 0);
  const int tg = blockIdx.x >> 2, hg = blockIdx.x & 3;
  STAMP0(0);
  if (threadIdx.x == 512) {
    #pragma unroll 1
    for (uint32_t b = B_X; b < B_F + 32; b += 8) mbar_init(sb + b, (b >= B_E && b < B_R) ? 8 : (b >= B_REL && b < B_F) ? 16 : 1);
    asm volatile("fence.mbarrier_init.release.cluster;" ::: "memory");
    proxy_fence();
    mbar_expect(sb + B_R, 43776);
    bulk(sb, wk, 20736, sb + B_R); bulk(sb + 20736, wv, 20736, sb + B_R); bulk(sb + 41472, wr, 1152, sb + B_R); bulk(sb + 42624, gw, 1152, sb + B_R);
    #pragma unroll 1
    for (int c = 0; c < 9; c++) { mbar_expect(sb + B_X + c * 8, 8192); tma2(sb + S_X + c * 8192, &mp.x, c * 64, tg * 64, sb + B_X + c * 8); }
  }
  __syncthreads();
  STAMP0(11);
  if (wg == 4) {
    asm volatile("setmaxnreg.dec.sync.aligned.u32 32;");
    const int tid = threadIdx.x - 512, warp = tid >> 5, lane = tid & 31;
    if (tid == 0) {
      #pragma unroll 1
      for (int c = 0; c < 9; c++) {
        if (c >= 4) mbar_wait(sb + B_E + (c - 4) * 8, 0);
        mbar_expect(sb + B_W + c * 8, 24576);
        #pragma unroll
        for (int j = 0; j < 3; j++) tma3(sb + wslotA(c) + j * 8192, &mp.wq, j * 64, hg, c * 64, sb + B_W + c * 8);
      }
    } else if (warp == 1) {
      if (lane == 0) {
        await(0, NCTA);
        STAMP(3);
        #pragma unroll
        for (int c = 0; c < 2; c++) { mbar_expect(sb + B_KV + c * 8, CH); bulk(sb + c * CH, g_kv + c * 1280, CH, sb + B_KV + c * 8); }
      }
      __syncwarp();
      float k2 = 0.f, vm = 0.f, r = -INFINITY; int ri = 0;
      #pragma unroll
      for (int i = 0; i < 4; i++) {
        float4 s = __ldcg(g_stat + i * 32 + lane);
        k2 = fmaxf(k2, s.x); vm = fmaxf(vm, s.y);
        if (s.z > r) { r = s.z; ri = __float_as_int(s.w); }
      }
      const float2 gt = __ldcg((const float2*)(g_gate + tg * 64) + lane);
      bar_sync(3, 416);
      if (lane == 0) {
        #pragma unroll 1
        for (int c = 2; c < 8; c++) { mbar_expect(sb + B_KV + c * 8, CH); bulk(sb + c * CH, g_kv + c * 1280, CH, sb + B_KV + c * 8); }
      }
      #pragma unroll
      for (int o = 16; o; o >>= 1) {
        k2 = fmaxf(k2, __shfl_xor_sync(~0u, k2, o)); vm = fmaxf(vm, __shfl_xor_sync(~0u, vm, o));
        float r2 = __shfl_xor_sync(~0u, r, o); int i2 = __shfl_xor_sync(~0u, ri, o);
        if (r2 > r || (r2 == r && i2 < ri)) { r = r2; ri = i2; }
      }
      if (lane == 0) *(float4*)(smem + S_ST) = make_float4(k2, vm, r, __int_as_float(ri & (SEQ - 1)));
      ((float2*)(smem + S_G))[lane] = gt;
      bar_sync(4, 544);
      if (lane == 0) signal(3);
      __syncwarp();
    }
    bar_sync(1, 128);
    const int idx = *(volatile int*)(smem + S_ST + 12);
    if (blockIdx.x < NSL) {
      if (tid == 0) {
        mbar_wait(sb + B_KV + 56, 0);
        #pragma unroll 1
        for (int i = 0; i < 4; i++) ffn_load(sb, mp, i);
      }
      if (tid < 72) *(uint4*)(smem + S_XS + tid * 16) = ldg16(x + (size_t)idx * DM + tid * 8);
      proxy_fence();
      bar_sync(1, 128);
      float acc[4], gt0 = 0.f, gt1 = 0.f;
      #pragma unroll 1
      for (int i = 0; i < 27; i++) {
        if (i == 0 || i == 9 || i >= 18) {
          #pragma unroll
          for (int k = 0; k < 4; k++) asm volatile("mov.b32 %0, 0;" : "=f"(acc[k]));
        }
        const uint32_t alo = ((sb + S_FFN + (i & 3) * 8192) >> 4) | (64u << 16);
        const uint32_t blo = ((sb + (i < 18 ? S_XS + (i < 9 ? i : i - 9) * 128 : S_H)) >> 4) | (1u << 16);
        mbar_wait(sb + B_F + (i & 3) * 8, (i >> 2) & 1);
        wg_fence();
        #pragma unroll
        for (int k = 0; k < 4; k++) wg_ss8(acc, mk64(alo + k * 128, 64u | (1u << 30)), mk64(blo + k * 2, 8));
        wg_commit(); wg_wait<0>(); fence_regs<4>(acc);
        const int row = warp * 16 + (lane >> 2);
        if (i == 8) { gt0 = bfr(acc[0]); gt1 = bfr(acc[2]); }
        if (i == 17) {
          if ((lane & 3) == 0) {
            __nv_bfloat16* hh = (__nv_bfloat16*)(smem + S_H);
            hh[row] = __float2bfloat16(bfr(__fdividef(gt0, 1.f + __expf(-gt0))) * bfr(acc[0]));
            hh[row + 8] = __float2bfloat16(bfr(__fdividef(gt1, 1.f + __expf(-gt1))) * bfr(acc[2]));
          }
          proxy_fence();
        }
        if (i >= 18 && (lane & 3) == 0) { float* yp = g_ypart + blockIdx.x * DM + (i - 18) * 64 + row; yp[0] = acc[0]; yp[8] = acc[2]; }
        bar_sync(1, 128);
        if (tid == 0 && i < 23) ffn_load(sb, mp, i + 4);
      }
      if (tid == 0) { signal(1); STAMP(5); }
    }
    if ((idx >> 6) == tg) {
      if (tid == 0) await(1, NSL);
      bar_sync(1, 128);
      float4* red = (float4*)(smem + S_FFN + 24 * KB);
      if (tid < 108) {
        const float4* yp = (const float4*)(g_ypart + (tid / 36) * 24 * DM + hg * 144) + tid % 36;
        float4 a = make_float4(0.f, 0.f, 0.f, 0.f);
        #pragma unroll 4
        for (int i = 0; i < 24; i++) { float4 b = __ldcg(yp + i * (DM / 4)); a.x += b.x; a.y += b.y; a.z += b.z; a.w += b.w; }
        red[tid] = a;
      }
      bar_sync(1, 128);
      const float rs = bfr(__fdividef(1.f, 1.f + __expf(-bfr(*(volatile float*)(smem + S_ST + 8)))));
      for (int i = tid; i < 144; i += 128) { const float* f = (const float*)red + i; ((float*)(smem + S_Y))[i] = bfr(bfr(f[0] + f[144] + f[288]) * rs); }
    }
    bar_arrive(5, 640);
    if (tid == 0) {
      #pragma unroll 1
      for (int u = 0; u < 9; u++) {
        const int c = u == 0 ? 5 : u < 6 ? u - 1 : u;
        if (c < 5) mbar_wait(sb + B_REL + (c + 1) * 8, 0);
        if (c > 5) mbar_wait(sb + B_E + (c - 6) * 8, 1);
        mbar_expect(sb + B_W + c * 8, 24576);
        #pragma unroll
        for (int j = 0; j < 3; j++) tma3(sb + wslotC(c) + j * 8192, &mp.wo, j * 64, hg, c * 64, sb + B_W + c * 8);
        if (u == 5) {
          await(8 + tg, 4);
          STAMP(18);
          #pragma unroll 1
          for (int k = 0; k < 9; k++) { mbar_expect(sb + B_X + k * 8, 8192); tma2(sb + oslot(k), &mp.o, k * 64, tg * 64, sb + B_X + k * 8); }
        }
      }
      unsigned old;
      asm volatile("atom.add.acq_rel.gpu.global.u32 %0, [%1], 1;" : "=r"(old) : "l"(g_cnt + 64) : "memory");
      if (old == NCTA - 1) {
        #pragma unroll 1
        for (int i = 0; i < 40; i++) g_cnt[i * 32] = 0;
      }
    }
  } else {
    asm volatile("setmaxnreg.inc.sync.aligned.u32 112;");
    const int warp = (threadIdx.x >> 5) & 3, lane = threadIdx.x & 31, g = lane >> 2, t = lane & 3;
    uint32_t* sq = (uint32_t*)(smem + S_Q) + (warp * 16 + g) * QP;
    if (wg == 0) {
      gemm<false, 0>(sb, sq + t);
      STAMP0(4);
    } else if (wg == 1) {
      gemm<false, 1>(sb, sq + t);
    } else if (wg == 3) {
      special(smem, sb, tg * 64 + hg * 16, hg * 16);
      if (threadIdx.x == 384) STAMP(2);
      bar_arrive(3, 416);
    }
    bar_sync(6, 512);
    STAMP0(7);
    volatile uint32_t* stash = (volatile uint32_t*)(smem + S_FLAG) + threadIdx.x;
    volatile uint8_t* fl = smem + S_FLAG - 512 + threadIdx.x;
    const uint32_t sb16 = sb >> 4;
    const int q0 = tg * 64 + warp * 16;
    uint32_t qa[8];
    stash[0] = 0; qa[6] = stash[0]; qa[7] = stash[0];
    {
      const float QS = 0.23570226f * 1.44269504f;
      float n[2][2];
      uint32_t qh[2];
      #pragma unroll
      for (int i = 1; i >= 0; i--) {
        const uint32_t* qp = sq + (i * 4 + wg) * 9;
        uint32_t raw[6] = {qp[t], qp[8 * QP + t], qp[t + 4], qp[8 * QP + t + 4], t == 0 ? qp[8] : 0u, t == 0 ? qp[8 * QP + 8] : 0u};
        n[i][0] = n[i][1] = 0.f;
        #pragma unroll
        for (int j = 0; j < 6; j++) {
          float a = bflo(raw[j]), b = bfhi(raw[j]);
          n[i][j & 1] += a * a + b * b;
          qa[j] = pack2h(a * (QS / 32.f), b * (QS / 32.f));
        }
        #pragma unroll
        for (int r = 0; r < 2; r++) {
          n[i][r] += __shfl_xor_sync(~0u, n[i][r], 1); n[i][r] += __shfl_xor_sync(~0u, n[i][r], 2);
          n[i][r] = n[i][r] <= 65536.f ? sqrta(n[i][r]) : INFINITY;
        }
        if (i) {
          #pragma unroll
          for (int j = 0; j < 4; j++) stash[j * 512] = qa[j];
          qh[0] = qa[4]; qh[1] = qa[5];
        }
      }
      bar_sync(4, 544);
      const float2 st = *(const float2*)(smem + S_ST);
      const bool kvbad = !(st.x <= 65536.f) || !(st.y <= 16384.f) || !(st.y >= 0.015625f);
      const float kn = sqrta(st.x) * (QS * 1.01f * 8.f);
      uint32_t flags = 0;
      #pragma unroll
      for (int i = 0; i < 2; i++) {
        #pragma unroll
        for (int r = 0; r < 2; r++) {
          float M = ceilf(n[i][r] * kn) * 0.125f;
          if (kvbad || !(M <= 40.f)) { flags |= 1u << (3 * i); M = 0.f; }
          if (M > 14.f) { flags |= 2u << (3 * i + r); M = 28.f - M; }
          if (t == 1) (i ? qh[r] : qa[4 + r]) = pack2h(M, M - 13.f);
        }
      }
      stash[4 * 512] = qh[0]; stash[5 * 512] = qh[1];
      *fl = flags;
    }
    uint32_t s0[16], s1[16], p0[16], p1[16];
    STAMP0(14);
    mbar_wait(sb + B_KV, 0);
    STAMP0(19);
    wg_fence(); qk64(s0, qa, sb16); wg_commit();
    #pragma unroll
    for (int i = 0; i < 2; i++) {
      float o[12];
      #pragma unroll
      for (int k = 0; k < 12; k++) asm volatile("mov.b32 %0, 0;" : "=f"(o[k]));
      wg_wait<0>(); fence_regs<16>(s0);
      STAMP0(9 + 3 * i);
      #pragma unroll 1
      for (int c = 0; c < 8; c++) {
        const uint32_t a0 = sb16 + c * (CH >> 4), an = c == 7 ? sb16 : a0 + (CH >> 4);
        wg_fence(); qk64(s1, qa, a0 + 64); wg_commit();
        softmax64(s0, p0); fence_regs<16>(p0);
        wg_fence(); pv64(o, p0, a0); PVC qk64(s0, qa, a0 + 128); wg_commit();
        wg_wait<WN>(); fence_regs<16>(s1);
        if (i == 1 && lane == 0 && c) mbar_arrive(sb + B_REL + 8 * c - 8);
        softmax64(s1, p1); fence_regs<16>(p1);
        wg_fence(); pv64(o, p1, a0 + 64); PVC qk64(s1, qa, a0 + 192); wg_commit();
        wg_wait<WN>(); fence_regs<16>(s0);
        softmax64(s0, p0); fence_regs<16>(p0);
        if (i == 0 && c < 7) mbar_wait(sb + B_KV + 8 * c + 8, 0);
        wg_fence(); pv64(o, p0, a0 + 128); PVC qk64(s0, qa, an); wg_commit();
        wg_wait<WN>(); fence_regs<16>(s1);
        softmax64(s1, p1); fence_regs<16>(p1);
        wg_fence(); pv64(o, p1, a0 + 192); wg_commit();
        wg_wait<1>(); fence_regs<16>(s0);
      }
      wg_wait<0>();
      fence_regs<12>(o);
      RETID
      if (i == 0) {
        #pragma unroll
        for (int j = 0; j < 6; j++) qa[j] = stash[j * 512];
        stash[0] = 0; qa[6] = stash[0]; qa[7] = stash[0];
        wg_fence(); qk64(s0, qa, sb16); wg_commit();
      }
      STAMP0(10 + 3 * i);
      const uint32_t flags = *fl;
      float l0 = __shfl_sync(0xffffffffu, o[0], lane | 3), l1 = __shfl_sync(0xffffffffu, o[2], lane | 3);
      bool bad = ((flags >> (3 * i)) & 1) || !(l0 <= 3e38f) || !(l1 <= 3e38f) || !(l0 > 0.f) || !(l1 > 0.f)
                 || (((flags >> (3 * i + 1)) & 1) && l0 < 256.f) || (((flags >> (3 * i + 2)) & 1) && l1 < 256.f);
      if (__any_sync(0xffffffffu, bad)) *fl = flags | (64u << i);
      else {
        float r0 = __fdividef(1.f, l0), r1 = __fdividef(1.f, l1);
        uint32_t* op0 = (uint32_t*)(g_o + (size_t)(q0 + g) * DM + (hg * 8 + i * 4 + wg) * 18);
        uint32_t* op1 = op0 + 4 * DM;
        op0[t] = pack2(o[4] * r0, o[5] * r0); op1[t] = pack2(o[6] * r1, o[7] * r1);
        op0[t + 4] = pack2(o[8] * r0, o[9] * r0); op1[t + 4] = pack2(o[10] * r1, o[11] * r1);
        if (t == 2) { op0[8] = pack2(o[0] * r0, o[1] * r0); op1[8] = pack2(o[2] * r1, o[3] * r1); }
      }
    }
    {
    RETID
    uint32_t* sq2 = (uint32_t*)(smem + S_Q) + (warp * 16 + g) * QP;
    {
      const uint32_t flags = *fl;
      if (flags >> 6) await(3, NCTA);
      #pragma unroll 1
      for (int i = 0; i < 2; i++)
        if ((flags >> (6 + i)) & 1) attn_exact((const __nv_bfloat16*)(smem + S_Q) + warp * 32 * QP + (i * 4 + wg) * 18, q0, hg * 8 + i * 4 + wg, lane);
    }
    if ((tx_ & 127) == 0 && wg) STAMP(14 + wg);
    bar_sync(6, 512);
    if (tx_ == 384) signal(8 + tg);
    uint4 xr[3];
    #pragma unroll
    for (int u = 0; u < 3; u++) {
      const int v = tx_ + u * 512, row = v / 18, c8 = v % 18;
      if (v < 1152) xr[u] = ldg16(x + (size_t)(tg * 64 + row) * DM + hg * 144 + c8 * 8);
    }
    if (wg == 0) gemm<true, 0>(sb, sq2 + t);
    if (wg == 1) gemm<true, 1>(sb, sq2 + t);
    STAMP0(20);
    bar_sync(5, 640);
    const int li = *(const int*)(smem + S_ST + 12) - tg * 64;
    #pragma unroll
    for (int u = 0; u < 3; u++) {
      const int v = tx_ + u * 512, row = v / 18, c8 = v % 18;
      if (v < 1152) {
        const float gg = ((const float*)(smem + S_G))[row];
        const uint4 av = *(const uint4*)(smem + S_Q + row * (QP * 4) + c8 * 16);
        const uint32_t aa[4] = {av.x, av.y, av.z, av.w}, xx[4] = {xr[u].x, xr[u].y, xr[u].z, xr[u].w};
        uint32_t r[4];
        #pragma unroll
        for (int k = 0; k < 4; k++) {
          float b0 = bflo(xx[k]), b1 = bfhi(xx[k]);
          if (row == li) { const float* ys = (const float*)(smem + S_Y) + c8 * 8 + 2 * k; b0 += ys[0]; b1 += ys[1]; }
          r[k] = pack2(fmaf(gg, bflo(aa[k]) - b0, b0), fmaf(gg, bfhi(aa[k]) - b1, b1));
        }
        *(uint4*)(out + (size_t)(tg * 64 + row) * DM + hg * 144 + c8 * 8) = make_uint4(r[0], r[1], r[2], r[3]);
      }
    }
    }
    STAMP0(21);
  }
}

typedef CUresult (*EncFn)(CUtensorMap*, CUtensorMapDataType, cuuint32_t, void*, const cuuint64_t*, const cuuint64_t*, const cuuint32_t*, const cuuint32_t*,
                          CUtensorMapInterleave, CUtensorMapSwizzle, CUtensorMapL2promotion, CUtensorMapFloatOOBfill);
static void make_map(EncFn enc, CUtensorMap* m, const void* base, int cols, int rows, bool grouped) {
  cuuint64_t d2[2] = {(cuuint64_t)cols, (cuuint64_t)rows}, s2[1] = {(cuuint64_t)cols * 2}, d3[3] = {144, 4, (cuuint64_t)rows}, s3[2] = {288, (cuuint64_t)cols * 2};
  cuuint32_t b2[2] = {64, 64}, b3[3] = {64, 1, 64}, es[3] = {1, 1, 1};
  enc(m, CU_TENSOR_MAP_DATA_TYPE_BFLOAT16, grouped ? 3 : 2, (void*)base, grouped ? d3 : d2, grouped ? s3 : s2, grouped ? b3 : b2, es, CU_TENSOR_MAP_INTERLEAVE_NONE,
      CU_TENSOR_MAP_SWIZZLE_128B, CU_TENSOR_MAP_L2_PROMOTION_L2_256B, CU_TENSOR_MAP_FLOAT_OOB_FILL_NONE);
}

extern "C" void kernel_launch(void* const* d_in, const int* in_sizes, int n_in, void* d_out, int out_size) {
  typedef const __nv_bfloat16* P;
  static EncFn enc = nullptr;
  static void* po = nullptr;
  if (!enc) {
    cudaDriverEntryPointQueryResult qr;
    cudaGetDriverEntryPoint("cuTensorMapEncodeTiled", (void**)&enc, cudaEnableDefault, &qr);
    cudaGetSymbolAddress(&po, g_o);
    cudaFuncSetAttribute(k_fused, cudaFuncAttributeMaxDynamicSharedMemorySize, SMEM);
  }
  Maps mp;
  make_map(enc, &mp.x, d_in[0], DM, SEQ, false); make_map(enc, &mp.wq, d_in[1], DM, DM, true); make_map(enc, &mp.wo, d_in[4], DM, DM, true);
  make_map(enc, &mp.o, po, DM, SEQ, false); make_map(enc, &mp.wg, d_in[7], FF, DM, false); make_map(enc, &mp.wu, d_in[8], FF, DM, false);
  make_map(enc, &mp.wd, d_in[9], DM, FF, false);
  k_fused<<<NCTA, 640, SMEM, cudaStreamPerThread>>>(mp, (P)d_in[0], (P)d_in[2], (P)d_in[3], (P)d_in[6], (P)d_in[10], (__nv_bfloat16*)d_out);
}
```

```cpp
#include <cuda_runtime.h>
#include <cuda_bf16.h>
#include <cuda_fp16.h>
#include <stdint.h>
#include <cuda.h>

constexpr int SEQ = 2048, DM = 576, FF = 4608, NSL = 72, NCTA = 128;
constexpr uint32_t KMASK = 0x25;

__device__ __align__(128) __nv_bfloat16 g_o[SEQ * DM];
__device__ uint4 g_kv[5 * SEQ];
__device__ float g_kraw[SEQ * 18];
__device__ float g_vraw[SEQ * 18];
__device__ float g_gate[SEQ];
__device__ float4 g_stat[NCTA];
__device__ float g_ypart[NSL * DM];
__device__ __align__(128) unsigned g_cnt[40 * 32];

#define STAMP(k)
#define STAMP0(k)
__device__ __forceinline__ void wgh_n64_sd0(uint32_t* d, uint32_t a0, uint32_t a1, uint32_t a2, uint32_t a3, uint64_t bdesc) {
  asm volatile("{\n.reg .pred p;\nsetp.ne.b32 p, 0, 0;\n"
    "wgmma.mma_async.sync.aligned.m64n64k16.f16.f16.f16 {%0, %1, %2, %3, %4, %5, %6, %7, %8, %9, %10, %11, %12, %13, %14, %15}, {%16, %17, %18, %19}, %20, p, 1, 1, 0;\n}\n"
    : "=r"(d[0]), "=r"(d[1]), "=r"(d[2]), "=r"(d[3]), "=r"(d[4]), "=r"(d[5]), "=r"(d[6]), "=r"(d[7]), "=r"(d[8]), "=r"(d[9]), "=r"(d[10]), "=r"(d[11]), "=r"(d[12]), "=r"(d[13]), "=r"(d[14]), "=r"(d[15]) : "r"(a0), "r"(a1), "r"(a2), "r"(a3), "l"(bdesc));
}
__device__ __forceinline__ void wgh_n64_sd1(uint32_t* d, uint32_t a0, uint32_t a1, uint32_t a2, uint32_t a3, uint64_t bdesc) {
  asm volatile("{\n.reg .pred p;\nsetp.ne.b32 p, 1, 0;\n"
    "wgmma.mma_async.sync.aligned.m64n64k16.f16.f16.f16 {%0, %1, %2, %3, %4, %5, %6, %7, %8, %9, %10, %11, %12, %13, %14, %15}, {%16, %17, %18, %19}, %20, p, 1, 1, 0;\n}\n"
    : "+r"(d[0]), "+r"(d[1]), "+r"(d[2]), "+r"(d[3]), "+r"(d[4]), "+r"(d[5]), "+r"(d[6]), "+r"(d[7]), "+r"(d[8]), "+r"(d[9]), "+r"(d[10]), "+r"(d[11]), "+r"(d[12]), "+r"(d[13]), "+r"(d[14]), "+r"(d[15]) : "r"(a0), "r"(a1), "r"(a2), "r"(a3), "l"(bdesc));
}
__device__ __forceinline__ void wg_pv(float* d, uint32_t a0, uint32_t a1, uint32_t a2, uint32_t a3, uint64_t bdesc) {
  asm volatile("{\n.reg .pred p;\nsetp.ne.b32 p, 1, 0;\n"
    "wgmma.mma_async.sync.aligned.m64n24k16.f32.f16.f16 {%0, %1, %2, %3, %4, %5, %6, %7, %8, %9, %10, %11}, {%12, %13, %14, %15}, %16, p, 1, 1, 1;\n}\n"
    : "+f"(d[0]), "+f"(d[1]), "+f"(d[2]), "+f"(d[3]), "+f"(d[4]), "+f"(d[5]), "+f"(d[6]), "+f"(d[7]), "+f"(d[8]), "+f"(d[9]), "+f"(d[10]), "+f"(d[11]) : "r"(a0), "r"(a1), "r"(a2), "r"(a3), "l"(bdesc));
}
__device__ __forceinline__ void wg_ss64(float* d, uint64_t adesc, uint64_t bdesc) {
  asm volatile("{\n.reg .pred p;\nsetp.ne.b32 p, 1, 0;\n"
    "wgmma.mma_async.sync.aligned.m64n64k16.f32.bf16.bf16 {%0, %1, %2, %3, %4, %5, %6, %7, %8, %9, %10, %11, %12, %13, %14, %15, %16, %17, %18, %19, %20, %21, %22, %23, %24, %25, %26, %27, %28, %29, %30, %31}, %32, %33, p, 1, 1, 0, 1;\n}\n"
    : "+f"(d[0]), "+f"(d[1]), "+f"(d[2]), "+f"(d[3]), "+f"(d[4]), "+f"(d[5]), "+f"(d[6]), "+f"(d[7]), "+f"(d[8]), "+f"(d[9]), "+f"(d[10]), "+f"(d[11]), "+f"(d[12]), "+f"(d[13]), "+f"(d[14]), "+f"(d[15]), "+f"(d[16]), "+f"(d[17]), "+f"(d[18]), "+f"(d[19]), "+f"(d[20]), "+f"(d[21]), "+f"(d[22]), "+f"(d[23]), "+f"(d[24]), "+f"(d[25]), "+f"(d[26]), "+f"(d[27]), "+f"(d[28]), "+f"(d[29]), "+f"(d[30]), "+f"(d[31]) : "l"(adesc), "l"(bdesc));
}
__device__ __forceinline__ void wg_ss80(float* d, uint64_t adesc, uint64_t bdesc) {
  asm volatile("{\n.reg .pred p;\nsetp.ne.b32 p, 1, 0;\n"
    "wgmma.mma_async.sync.aligned.m64n80k16.f32.bf16.bf16 {%0, %1, %2, %3, %4, %5, %6, %7, %8, %9, %10, %11, %12, %13, %14, %15, %16, %17, %18, %19, %20, %21, %22, %23, %24, %25, %26, %27, %28, %29, %30, %31, %32, %33, %34, %35, %36, %37, %38, %39}, %40, %41, p, 1, 1, 0, 1;\n}\n"
    : "+f"(d[0]), "+f"(d[1]), "+f"(d[2]), "+f"(d[3]), "+f"(d[4]), "+f"(d[5]), "+f"(d[6]), "+f"(d[7]), "+f"(d[8]), "+f"(d[9]), "+f"(d[10]), "+f"(d[11]), "+f"(d[12]), "+f"(d[13]), "+f"(d[14]), "+f"(d[15]), "+f"(d[16]), "+f"(d[17]), "+f"(d[18]), "+f"(d[19]), "+f"(d[20]), "+f"(d[21]), "+f"(d[22]), "+f"(d[23]), "+f"(d[24]), "+f"(d[25]), "+f"(d[26]), "+f"(d[27]), "+f"(d[28]), "+f"(d[29]), "+f"(d[30]), "+f"(d[31]), "+f"(d[32]), "+f"(d[33]), "+f"(d[34]), "+f"(d[35]), "+f"(d[36]), "+f"(d[37]), "+f"(d[38]), "+f"(d[39]) : "l"(adesc), "l"(bdesc));
}
__device__ __forceinline__ void wg_ss8(float* d, uint64_t adesc, uint64_t bdesc) {
  asm volatile("{\n.reg .pred p;\nsetp.ne.b32 p, 1, 0;\n"
    "wgmma.mma_async.sync.aligned.m64n8k16.f32.bf16.bf16 {%0, %1, %2, %3}, %4, %5, p, 1, 1, 1, 0;\n}\n"
    : "+f"(d[0]), "+f"(d[1]), "+f"(d[2]), "+f"(d[3]) : "l"(adesc), "l"(bdesc));
}

__device__ __forceinline__ void wg_fence() { asm volatile("wgmma.fence.sync.aligned;" ::: "memory"); }
__device__ __forceinline__ void wg_commit() { asm volatile("wgmma.commit_group.sync.aligned;" ::: "memory"); }
template<int N> __device__ __forceinline__ void wg_wait() { asm volatile("wgmma.wait_group.sync.aligned %0;" :: "n"(N) : "memory"); }
__device__ __forceinline__ uint32_t pack2(float lo, float hi) { uint32_t r; asm("cvt.rn.bf16x2.f32 %0, %1, %2;" : "=r"(r) : "f"(hi), "f"(lo)); return r; }
__device__ __forceinline__ uint32_t pack2h(float lo, float hi) { uint32_t r; asm("cvt.rn.f16x2.f32 %0, %1, %2;" : "=r"(r) : "f"(hi), "f"(lo)); return r; }
__device__ __forceinline__ float bflo(uint32_t v) { return __uint_as_float(v << 16); }
__device__ __forceinline__ float bfhi(uint32_t v) { return __uint_as_float(v & 0xffff0000u); }
__device__ __forceinline__ float bfr(float v) { return __bfloat162float(__float2bfloat16(v)); }
__device__ __forceinline__ uint32_t hfma2(uint32_t a, uint32_t b, uint32_t c) { uint32_t r; asm("fma.rn.f16x2 %0, %1, %2, %3;" : "=r"(r) : "r"(a), "r"(b), "r"(c)); return r; }
__device__ __forceinline__ uint32_t hfma2r(uint32_t a, uint32_t b, uint32_t c) { uint32_t r; asm("fma.rn.relu.f16x2 %0, %1, %2, %3;" : "=r"(r) : "r"(a), "r"(b), "r"(c)); return r; }
__device__ __forceinline__ uint32_t ex2h2(uint32_t x) { uint32_t r; asm("ex2.approx.f16x2 %0, %1;" : "=r"(r) : "r"(x)); return r; }
__device__ __forceinline__ uint64_t mk64(uint32_t lo, uint32_t hi) { uint64_t d; asm("mov.b64 %0, {%1, %2};" : "=l"(d) : "r"(lo), "r"(hi)); return d; }
template<int N> __device__ __forceinline__ void fence_regs(float* r) {
  #pragma unroll
  for (int i = 0; i < N; i++) asm volatile("" : "+f"(r[i]) :: "memory");
}
template<int N> __device__ __forceinline__ void fence_regs(uint32_t* r) {
  #pragma unroll
  for (int i = 0; i < N; i++) asm volatile("" : "+r"(r[i]) :: "memory");
}
__device__ __forceinline__ void cp16(uint32_t dst, const void* src) { asm volatile("cp.async.cg.shared.global [%0], [%1], 16;" :: "r"(dst), "l"(src) : "memory"); }
__device__ __forceinline__ void cp4(uint32_t dst, const void* src) { asm volatile("cp.async.ca.shared.global [%0], [%1], 4;" :: "r"(dst), "l"(src) : "memory"); }
__device__ __forceinline__ void cp_commit() { asm volatile("cp.async.commit_group;" ::: "memory"); }
template<int N> __device__ __forceinline__ void cp_wait() { asm volatile("cp.async.wait_group %0;" :: "n"(N) : "memory"); }
__device__ __forceinline__ void proxy_fence() { asm volatile("fence.proxy.async.shared::cta;" ::: "memory"); }
__device__ __forceinline__ void pdl_wait() { asm volatile("griddepcontrol.wait;" ::: "memory"); }
__device__ __forceinline__ void pdl_go() { asm volatile("griddepcontrol.launch_dependents;" ::: "memory"); }
__device__ __forceinline__ uint4 ldg16(const void* p) { uint4 v; asm volatile("ld.global.nc.L1::no_allocate.v4.u32 {%0,%1,%2,%3}, [%4];" : "=r"(v.x), "=r"(v.y), "=r"(v.z), "=r"(v.w) : "l"(p)); return v; }
__device__ __forceinline__ uint4 ldg16c(const void* p) { uint4 v; asm volatile("ld.global.L1::no_allocate.v4.u32 {%0,%1,%2,%3}, [%4];" : "=r"(v.x), "=r"(v.y), "=r"(v.z), "=r"(v.w) : "l"(p) : "memory"); return v; }
__device__ __forceinline__ void mbar_wait(uint32_t bar, uint32_t parity) {
  #pragma unroll 1
  for (int it = 0; it < (1 << 22); it++) {
    uint32_t ok;
    asm volatile("{\n.reg .pred p;\nmbarrier.try_wait.parity.shared::cta.b64 p, [%1], %2;\nselp.u32 %0, 1, 0, p;\n}\n" : "=r"(ok) : "r"(bar), "r"(parity) : "memory");
    if (ok) break;
  }
}
__device__ __forceinline__ void mbar_init(uint32_t bar, uint32_t cnt) { asm volatile("mbarrier.init.shared::cta.b64 [%0], %1;" :: "r"(bar), "r"(cnt) : "memory"); }
__device__ __forceinline__ void mbar_expect(uint32_t bar, uint32_t bytes) { asm volatile("mbarrier.arrive.expect_tx.shared::cta.b64 _, [%0], %1;" :: "r"(bar), "r"(bytes) : "memory"); }
__device__ __forceinline__ void mbar_arrive(uint32_t bar) { asm volatile("mbarrier.arrive.shared::cta.b64 _, [%0];" :: "r"(bar) : "memory"); }
__device__ __forceinline__ void tma2(uint32_t dst, const CUtensorMap* m, int c0, int c1, uint32_t bar) {
  asm volatile("cp.async.bulk.tensor.2d.shared::cluster.global.mbarrier::complete_tx::bytes [%0], [%1, {%3, %4}], [%2];" :: "r"(dst), "l"(m), "r"(bar), "r"(c0), "r"(c1) : "memory");
}
__device__ __forceinline__ void tma3(uint32_t dst, const CUtensorMap* m, int c0, int c1, int c2, uint32_t bar) {
  asm volatile("cp.async.bulk.tensor.3d.shared::cluster.global.mbarrier::complete_tx::bytes [%0], [%1, {%3, %4, %5}], [%2];" :: "r"(dst), "l"(m), "r"(bar), "r"(c0), "r"(c1), "r"(c2) : "memory");
}
__device__ __forceinline__ void bulk(uint32_t dst, const void* src, uint32_t bytes, uint32_t bar) {
  asm volatile("cp.async.bulk.shared::cluster.global.mbarrier::complete_tx::bytes [%0], [%1], %2, [%3];" :: "r"(dst), "l"(src), "r"(bytes), "r"(bar) : "memory");
}
__device__ __forceinline__ void bar_sync(int id, int n) { asm volatile("bar.sync %0, %1;" :: "r"(id), "r"(n) : "memory"); }
__device__ __forceinline__ void bar_arrive(int id, int n) { asm volatile("bar.arrive %0, %1;" :: "r"(id), "r"(n) : "memory"); }
__device__ __forceinline__ void proxy_fence_all() { asm volatile("fence.proxy.async;" ::: "memory"); }
__device__ __forceinline__ void signal(int i) {
  asm volatile("fence.acq_rel.gpu;\nred.relaxed.gpu.global.add.u32 [%0], 1;" :: "l"(g_cnt + i * 32) : "memory");
}
__device__ __forceinline__ void await(int i, unsigned n) {
  #pragma unroll 1
  for (int it = 0; it < (1 << 21); it++) {
    unsigned v; asm volatile("ld.acquire.gpu.global.u32 %0, [%1];" : "=r"(v) : "l"(g_cnt + i * 32) : "memory");
    if (v >= n) break;
  }
  proxy_fence_all();
}
__device__ __forceinline__ void ldsm4(uint32_t a, uint32_t* r) {
  asm volatile("ldmatrix.sync.aligned.m8n8.x4.shared.b16 {%0,%1,%2,%3}, [%4];" : "=r"(r[0]), "=r"(r[1]), "=r"(r[2]), "=r"(r[3]) : "r"(a) : "memory");
}
__device__ __forceinline__ void mma16(float* d, const uint32_t* a, uint32_t b0, uint32_t b1) {
  asm volatile("mma.sync.aligned.m16n8k16.row.col.f32.bf16.bf16.f32 {%0,%1,%2,%3}, {%4,%5,%6,%7}, {%8,%9}, {%0,%1,%2,%3};"
    : "+f"(d[0]), "+f"(d[1]), "+f"(d[2]), "+f"(d[3]) : "r"(a[0]), "r"(a[1]), "r"(a[2]), "r"(a[3]), "r"(b0), "r"(b1));
}

constexpr uint32_t KB = 1024, CH = 20480;
constexpr uint32_t S_X = 44 * KB, S_W = 116 * KB;
constexpr uint32_t S_FFN = 160 * KB, S_Q = 192 * KB, S_FLAG = 212 * KB, S_BAR = 224 * KB;
constexpr uint32_t B_X = S_BAR, B_W = B_X + 72, B_E = B_W + 72, B_R = B_E + 40, B_KV = B_R + 8, B_REL = B_KV + 64, B_F = B_REL + 56;
constexpr uint32_t S_ST = S_BAR + 352, S_G = S_BAR + 384, S_Y = S_G + 256, S_H = S_Y + 576, S_XS = S_H + 128, SMEM = S_XS + 1152 + 128;
constexpr int QP = 76;
__device__ __forceinline__ uint32_t wslotA(int c) { return S_W + (c & 3) * 24 * KB; }
__device__ __forceinline__ uint32_t wslotC(int c) { return c == 5 ? S_FFN : (c < 5 ? c : c - 6) * 24 * KB; }
__device__ __forceinline__ uint32_t oslot(int c) { return (c < 5 ? 120 + 8 * c : 152 + 8 * c) * KB; }

template<bool C, int W> __device__ __forceinline__ void gemm(uint32_t sb, uint32_t* sq) {
  constexpr int NA = W ? 40 : 32;
  float acc[NA];
  #pragma unroll
  for (int i = 0; i < NA; i++) asm volatile("mov.b32 %0, 0;" : "=f"(acc[i]));
  const uint32_t hi = 64u | (1u << 30);
  #pragma unroll
  for (int c = 0; c < 9; c++) {
    const uint32_t alo = ((sb + (C ? oslot(c) : S_X + c * 8192)) >> 4) | (1u << 16), blo = ((sb + (C ? wslotC(c) : wslotA(c)) + W * 8192) >> 4) | (512u << 16);
    mbar_wait(sb + B_X + c * 8, C);
    mbar_wait(sb + B_W + c * 8, C);
    wg_fence();
    #pragma unroll
    for (int k = 0; k < 4; k++) { if (W) wg_ss80(acc, mk64(alo + k * 2, hi), mk64(blo + k * 128, hi)); else wg_ss64(acc, mk64(alo + k * 2, hi), mk64(blo + k * 128, hi)); }
    wg_commit();
    if (c >= 1 && c <= (C ? 3 : 5)) { wg_wait<1>(); if ((threadIdx.x & 31) == 0) mbar_arrive(sb + B_E + (c - 1) * 8); }
  }
  wg_wait<0>();
  fence_regs<NA>(acc);
  if (!C && !W) STAMP0(22);
  if (!C) bar_arrive(3, 416);
  bar_sync(7, 256);
  #pragma unroll
  for (int j = 0; j < NA / 4; j++) { sq[W * 32 + j * 4] = pack2(acc[4*j], acc[4*j+1]); sq[8 * QP + W * 32 + j * 4] = pack2(acc[4*j+2], acc[4*j+3]); }
}

__device__ __forceinline__ void special(uint8_t* smem, uint32_t sb, int tok0, int row0) {
  const int tid = threadIdx.x & 127, warp = tid >> 5, lane = tid & 31, g = lane >> 2, t = lane & 3;
  float acc[6][4];
  #pragma unroll
  for (int i = 0; i < 6; i++) { acc[i][0] = acc[i][1] = acc[i][2] = acc[i][3] = 0.f; }
  const uint32_t* raw = (const uint32_t*)smem;
  const int r = row0 + (lane & 15);
  const uint32_t xa = sb + S_X + r * 128 + (((warp * 2 + (lane >> 4)) ^ (r & 7)) << 4);
  const int kb = warp * 16 + 2 * t;
  const uint32_t* pk = raw + kb * 9 + g;
  const uint32_t* pl = g < 2 ? raw + g * 5184 + kb * 9 + 8 : raw + 10368 + (g & 1) * 288 + (kb >> 1);
  const int ls = g < 2 ? 9 : 0, lc = g < 2 ? 576 : 32, l8 = g < 2 ? 72 : 4;
  const uint32_t se = g < 2 ? 0x5410 : 0x3210;
  mbar_wait(sb + B_R, 0);
  if (tid == 0) STAMP(1);
  #pragma unroll
  for (int c = 0; c < 9; c++) {
    uint32_t a[4];
    mbar_wait(sb + B_X + c * 8, 0);
    ldsm4(xa + c * 8192, a);
    #pragma unroll
    for (int m = 0; m < 2; m++) {
      const uint32_t* p = pk + m * 5184 + c * 576;
      uint32_t w0 = p[0], w1 = p[9], w2 = p[72], w3 = p[81];
      mma16(acc[2*m], a, __byte_perm(w0, w1, 0x5410), __byte_perm(w2, w3, 0x5410));
      mma16(acc[2*m+1], a, __byte_perm(w0, w1, 0x7632), __byte_perm(w2, w3, 0x7632));
    }
    const uint32_t* p = pl + c * lc;
    uint32_t w0 = p[0], w1 = p[ls], w2 = p[l8], w3 = p[l8 + ls];
    mma16(acc[4], a, __byte_perm(w0, w1, se), __byte_perm(w2, w3, se));
    mma16(acc[5], a, __byte_perm(w0, w1, 0x7632), __byte_perm(w2, w3, 0x7632));
  }
  if (tid == 0) STAMP(6);
  bar_sync(2, 128);
  float* part = (float*)smem;
  #pragma unroll
  for (int h = 0; h < 2; h++) {
    float* q = part + (warp * 16 + g + h * 8) * 44;
    *(float4*)(q + 4 * t) = make_float4(acc[0][2*h], acc[1][2*h], acc[0][2*h+1], acc[1][2*h+1]);
    *(float4*)(q + 16 + 4 * t) = make_float4(acc[2][2*h], acc[3][2*h], acc[2][2*h+1], acc[3][2*h+1]);
    if (t < 2) *(float2*)(q + 32 + 2 * t) = make_float2(acc[4][2*h], acc[4][2*h+1]);
    if (t == 0) *(float2*)(q + 36) = make_float2(acc[5][2*h], acc[5][2*h+1]);
  }
  bar_sync(2, 128);
  #pragma unroll
  for (int i = tid; i < 176; i += 128) {
    float4 a = ((float4*)part)[i], b = ((float4*)part)[i + 176], c = ((float4*)part)[i + 352], d = ((float4*)part)[i + 528];
    ((float4*)part)[i] = make_float4((a.x + b.x) + (c.x + d.x), (a.y + b.y) + (c.y + d.y), (a.z + b.z) + (c.z + d.z), (a.w + b.w) + (c.w + d.w));
  }
  bar_sync(2, 128);
  if (warp == 0) {
    const int isv = lane >> 4, key = tok0 + (lane & 15);
    const float* q = part + (lane & 15) * 44;
    float v[18];
    #pragma unroll
    for (int d = 0; d < 16; d++) v[d] = bfr(q[isv * 16 + d]);
    v[16] = bfr(q[32 + isv]); v[17] = bfr(q[36 + isv]);
    const bool mufu = (KMASK >> ((key >> 3) & 7)) & 1;
    const float sc = isv ? 1.f : mufu ? 32.f : 0.0625f;
    uint4* kv = g_kv + (key >> 8) * 1280 + (key & 255) + isv * 768;
    kv[0] = make_uint4(pack2h(v[0] * sc, v[1] * sc), pack2h(v[2] * sc, v[3] * sc), pack2h(v[4] * sc, v[5] * sc), pack2h(v[6] * sc, v[7] * sc));
    kv[256] = make_uint4(pack2h(v[8] * sc, v[9] * sc), pack2h(v[10] * sc, v[11] * sc), pack2h(v[12] * sc, v[13] * sc), pack2h(v[14] * sc, v[15] * sc));
    ((uint2*)(kv + 512 - isv * 768))[isv] = make_uint2(pack2h(v[16] * sc, v[17] * sc), isv ? 0x00003C00u : mufu ? 0x3C000000u : 0x00001800u);
    float s = 0.f, z = 0.f;
    #pragma unroll
    for (int d = 0; d < 18; d++) { s = isv ? fmaxf(s, fabsf(v[d])) : fmaf(v[d], v[d], s); z = fmaf(v[d], 0.f, z); }
    s += z;
    if (!(s <= 3e38f)) s = 3e38f;
    if (isv) g_gate[key] = __fdividef(1.f, 1.f + __expf(-bfr(q[35])));
    float rr = q[34]; int ri = key;
    #pragma unroll
    for (int o = 8; o; o >>= 1) {
      s = fmaxf(s, __shfl_xor_sync(~0u, s, o));
      float r2 = __shfl_xor_sync(~0u, rr, o); int i2 = __shfl_xor_sync(~0u, ri, o);
      if (r2 > rr || (r2 == rr && i2 < ri)) { rr = r2; ri = i2; }
    }
    const float vm = __shfl_xor_sync(~0u, s, 16);
    if (lane == 0) { g_stat[blockIdx.x] = make_float4(s, vm, rr, __int_as_float(ri)); atomicMax(g_cnt + 1, __float_as_uint(s)); atomicMax(g_cnt + 2, __float_as_uint(vm)); }
    __syncwarp();
    if (lane == 0) STAMP(8);
    if (lane == 0) signal(0);
    #pragma unroll
    for (int d = 0; d < 18; d++) (isv ? g_vraw : g_kraw)[d * SEQ + key] = v[d];
  }
}
__device__ __forceinline__ bool elect() { uint32_t p; asm volatile("{\n.reg .pred q;\nelect.sync _|q, 0xffffffff;\nselp.u32 %0, 1, 0, q;\n}" : "=r"(p)); return p; }
__device__ __forceinline__ float sqrta(float x) { float r; asm("sqrt.approx.f32 %0, %1;" : "=f"(r) : "f"(x)); return r; }
__device__ __forceinline__ uint32_t ex2poly(uint32_t x) {
  uint32_t t = hfma2r(x, 0x02000200u, 0u);
  uint32_t u = hfma2(t, 0xF800F800u, x);
  uint32_t e = hfma2r(u, 0x47AC47ACu, 0x29A029A0u);
  uint32_t p = hfma2(e, u, 0x08000800u);
  return p + __funnelshift_l(t, t, 10);
}
__device__ __forceinline__ void softmax64(const uint32_t* s, uint32_t* p) {
  #pragma unroll
  for (int j = 0; j < 8; j++) {
    if ((KMASK >> j) & 1) { p[2*j] = ex2h2(s[2*j]); p[2*j+1] = ex2h2(s[2*j+1]); }
    else { p[2*j] = ex2poly(s[2*j]); p[2*j+1] = ex2poly(s[2*j+1]); }
  }
}
__device__ __forceinline__ uint32_t kvt(int j) { return (j >> 2) * (CH >> 4) + (j & 3) * 64; }
__device__ __forceinline__ void qk64(uint32_t* s, const uint32_t* q, uint32_t a16) {
  uint32_t lo = a16 | (256u << 16);
  wgh_n64_sd0(s, q[0], q[1], q[2], q[3], mk64(lo, 8));
  wgh_n64_sd1(s, q[4], q[5], q[6], q[7], mk64(lo + 512, 8));
}
__device__ __forceinline__ void pv64(float* o, const uint32_t* p, uint32_t a16) {
  uint32_t lo = (a16 | (8u << 16)) + 512;
  #pragma unroll
  for (int j = 0; j < 4; j++) wg_pv(o, p[4*j], p[4*j+1], p[4*j+2], p[4*j+3], mk64(lo + j * 16, 256));
}
__device__ __forceinline__ void attn_exact(const __nv_bfloat16* sq, int q0, int h, int lane) {
  #pragma unroll 1
  for (int r = 0; r < 16; r++) {
    float q[18], o[18];
    #pragma unroll
    for (int d = 0; d < 18; d++) { q[d] = __bfloat162float(sq[r * 2 * QP + d]) * 0.23570226f; o[d] = 0.f; }
    float m = -INFINITY;
    #pragma unroll 1
    for (int k = lane; k < SEQ; k += 32) {
      float s = 0.f;
      #pragma unroll
      for (int d = 0; d < 18; d++) s = fmaf(q[d], __ldcg(g_kraw + d * SEQ + k), s);
      m = fmaxf(m, s);
    }
    #pragma unroll
    for (int x = 16; x; x >>= 1) m = fmaxf(m, __shfl_xor_sync(~0u, m, x));
    float l = 0.f;
    #pragma unroll 1
    for (int k = lane; k < SEQ; k += 32) {
      float s = 0.f;
      #pragma unroll
      for (int d = 0; d < 18; d++) s = fmaf(q[d], __ldcg(g_kraw + d * SEQ + k), s);
      float p = __expf(s - m);
      l += p;
      #pragma unroll
      for (int d = 0; d < 18; d++) o[d] = fmaf(p, __ldcg(g_vraw + d * SEQ + k), o[d]);
    }
    #pragma unroll
    for (int x = 16; x; x >>= 1) {
      l += __shfl_xor_sync(~0u, l, x);
      #pragma unroll
      for (int d = 0; d < 18; d++) o[d] += __shfl_xor_sync(~0u, o[d], x);
    }
    float inv = __fdividef(1.f, l), mine = 0.f;
    #pragma unroll
    for (int d = 0; d < 18; d++) if (lane == d) mine = o[d];
    if (lane < 18) g_o[(size_t)(q0 + r) * DM + h * 18 + lane] = __float2bfloat16(mine * inv);
  }
}

struct Maps { CUtensorMap x, wq, wo, o, wg, wu, wd; };

__device__ __forceinline__ void ffn_load(uint32_t sb, const Maps& mp, int i) {
  const uint32_t bar = sb + B_F + (i & 3) * 8, dst = sb + S_FFN + (i & 3) * 8192;
  mbar_expect(bar, 8192);
  if (i < 18) tma2(dst, i < 9 ? &mp.wg : &mp.wu, blockIdx.x * 64, (i < 9 ? i : i - 9) * 64, bar);
  else tma2(dst, &mp.wd, (i - 18) * 64, blockIdx.x * 64, bar);
}

#define RETID uint32_t tx_; asm volatile("mov.u32 %0, %%tid.x;" : "=r"(tx_)); const int warp = (tx_ >> 5) & 3, lane = tx_ & 31, g = lane >> 2, t = lane & 3, wg = tx_ >> 7, q0 = tg * 64 + warp * 16; \
  volatile uint32_t* stash = (volatile uint32_t*)(smem + S_FLAG) + tx_; volatile uint8_t* fl = smem + S_FLAG - 512 + tx_; (void)g; (void)t; (void)q0; (void)stash; (void)fl; (void)wg;
#define PVC wg_commit();
#define WN 2
__global__ void __launch_bounds__(640, 1) k_fused(const __grid_constant__ Maps mp, const __nv_bfloat16* __restrict__ x, const __nv_bfloat16* __restrict__ wk,
    const __nv_bfloat16* __restrict__ wv, const __nv_bfloat16* __restrict__ wr, const __nv_bfloat16* __restrict__ gw, __nv_bfloat16* __restrict__ out) {
  extern __shared__ __align__(1024) uint8_t smem[];
  const uint32_t sb = (uint32_t)__cvta_generic_to_shared(smem);
  const int wg = __shfl_sync(0xffffffffu, threadIdx.x >> 7, 0);
  const int tg = blockIdx.x >> 2, hg = blockIdx.x & 3;
  STAMP0(0);
  if (threadIdx.x == 512) {
    #pragma unroll 1
    for (uint32_t b = B_X; b < B_F + 32; b += 8) mbar_init(sb + b, (b >= B_E && b < B_R) ? 8 : (b >= B_REL && b < B_F) ? 16 : 1);
    asm volatile("fence.mbarrier_init.release.cluster;" ::: "memory");
    proxy_fence();
    mbar_expect(sb + B_R, 43776);
    bulk(sb, wk, 20736, sb + B_R); bulk(sb + 20736, wv, 20736, sb + B_R); bulk(sb + 41472, wr, 1152, sb + B_R); bulk(sb + 42624, gw, 1152, sb + B_R);
    #pragma unroll 1
    for (int c = 0; c < 9; c++) { mbar_expect(sb + B_X + c * 8, 8192); tma2(sb + S_X + c * 8192, &mp.x, c * 64, tg * 64, sb + B_X + c * 8); }
  }
  __syncthreads();
  STAMP0(11);
  if (wg == 4) {
    asm volatile("setmaxnreg.dec.sync.aligned.u32 32;");
    const int tid = threadIdx.x - 512, warp = tid >> 5, lane = tid & 31;
    if (tid == 0) {
      #pragma unroll 1
      for (int c = 0; c < 9; c++) {
        if (c >= 4) mbar_wait(sb + B_E + (c - 4) * 8, 0);
        mbar_expect(sb + B_W + c * 8, 24576);
        #pragma unroll
        for (int j = 0; j < 3; j++) tma3(sb + wslotA(c) + j * 8192, &mp.wq, j * 64, hg, c * 64, sb + B_W + c * 8);
      }
    } else if (warp == 1) {
      if (lane == 0) {
        uint32_t v0 = 0, v1 = 0, v2 = 0, v3;
        #pragma unroll 1
        for (int it = 0; it < (1 << 21) && v0 < NCTA; it++)
          asm volatile("ld.acquire.gpu.global.v4.u32 {%0,%1,%2,%3}, [%4];" : "=r"(v0), "=r"(v1), "=r"(v2), "=r"(v3) : "l"(g_cnt) : "memory");
        proxy_fence_all();
        STAMP(3);
        #pragma unroll
        for (int c = 0; c < 2; c++) { mbar_expect(sb + B_KV + c * 8, CH); bulk(sb + c * CH, g_kv + c * 1280, CH, sb + B_KV + c * 8); }
        *(uint2*)(smem + S_ST) = make_uint2(v1, v2);
      }
      __syncwarp();
      bar_arrive(4, 544);
      float r = -INFINITY; int ri = 0;
      #pragma unroll
      for (int i = 0; i < 4; i++) {
        float4 s = __ldcg(g_stat + i * 32 + lane);
        if (s.z > r) { r = s.z; ri = __float_as_int(s.w); }
      }
      const float2 gt = __ldcg((const float2*)(g_gate + tg * 64) + lane);
      bar_sync(3, 416);
      if (lane == 0) {
        #pragma unroll 1
        for (int c = 2; c < 8; c++) { mbar_expect(sb + B_KV + c * 8, CH); bulk(sb + c * CH, g_kv + c * 1280, CH, sb + B_KV + c * 8); }
      }
      #pragma unroll
      for (int o = 16; o; o >>= 1) {
        float r2 = __shfl_xor_sync(~0u, r, o); int i2 = __shfl_xor_sync(~0u, ri, o);
        if (r2 > r || (r2 == r && i2 < ri)) { r = r2; ri = i2; }
      }
      if (lane == 0) *(float2*)(smem + S_ST + 8) = make_float2(r, __int_as_float(ri & (SEQ - 1)));
      ((float2*)(smem + S_G))[lane] = gt;
      if (lane == 0) signal(3);
      __syncwarp();
    }
    bar_sync(1, 128);
    const int idx = *(volatile int*)(smem + S_ST + 12);
    if (blockIdx.x < NSL) {
      if (tid == 0) {
        mbar_wait(sb + B_KV + 56, 0);
        #pragma unroll 1
        for (int i = 0; i < 4; i++) ffn_load(sb, mp, i);
      }
      if (tid < 72) *(uint4*)(smem + S_XS + tid * 16) = ldg16(x + (size_t)idx * DM + tid * 8);
      proxy_fence();
      bar_sync(1, 128);
      float acc[4], gt0 = 0.f, gt1 = 0.f;
      #pragma unroll 1
      for (int i = 0; i < 27; i++) {
        if (i == 0 || i == 9 || i >= 18) {
          #pragma unroll
          for (int k = 0; k < 4; k++) asm volatile("mov.b32 %0, 0;" : "=f"(acc[k]));
        }
        const uint32_t alo = ((sb + S_FFN + (i & 3) * 8192) >> 4) | (64u << 16);
        const uint32_t blo = ((sb + (i < 18 ? S_XS + (i < 9 ? i : i - 9) * 128 : S_H)) >> 4) | (1u << 16);
        mbar_wait(sb + B_F + (i & 3) * 8, (i >> 2) & 1);
        wg_fence();
        #pragma unroll
        for (int k = 0; k < 4; k++) wg_ss8(acc, mk64(alo + k * 128, 64u | (1u << 30)), mk64(blo + k * 2, 8));
        wg_commit(); wg_wait<0>(); fence_regs<4>(acc);
        const int row = warp * 16 + (lane >> 2);
        if (i == 8) { gt0 = bfr(acc[0]); gt1 = bfr(acc[2]); }
        if (i == 17) {
          if ((lane & 3) == 0) {
            __nv_bfloat16* hh = (__nv_bfloat16*)(smem + S_H);
            hh[row] = __float2bfloat16(bfr(__fdividef(gt0, 1.f + __expf(-gt0))) * bfr(acc[0]));
            hh[row + 8] = __float2bfloat16(bfr(__fdividef(gt1, 1.f + __expf(-gt1))) * bfr(acc[2]));
          }
          proxy_fence();
        }
        if (i >= 18 && (lane & 3) == 0) { float* yp = g_ypart + blockIdx.x * DM + (i - 18) * 64 + row; yp[0] = acc[0]; yp[8] = acc[2]; }
        bar_sync(1, 128);
        if (tid == 0 && i < 23) ffn_load(sb, mp, i + 4);
      }
      if (tid == 0) { signal(1); STAMP(5); }
    }
    if ((idx >> 6) == tg) {
      if (tid == 0) await(1, NSL);
      bar_sync(1, 128);
      float4* red = (float4*)(smem + S_FFN + 24 * KB);
      if (tid < 108) {
        const float4* yp = (const float4*)(g_ypart + (tid / 36) * 24 * DM + hg * 144) + tid % 36;
        float4 a = make_float4(0.f, 0.f, 0.f, 0.f);
        #pragma unroll 4
        for (int i = 0; i < 24; i++) { float4 b = __ldcg(yp + i * (DM / 4)); a.x += b.x; a.y += b.y; a.z += b.z; a.w += b.w; }
        red[tid] = a;
      }
      bar_sync(1, 128);
      const float rs = bfr(__fdividef(1.f, 1.f + __expf(-bfr(*(volatile float*)(smem + S_ST + 8)))));
      for (int i = tid; i < 144; i += 128) { const float* f = (const float*)red + i; ((float*)(smem + S_Y))[i] = bfr(bfr(f[0] + f[144] + f[288]) * rs); }
    }
    bar_arrive(5, 640);
    if (tid == 0) {
      #pragma unroll 1
      for (int u = 0; u < 9; u++) {
        const int c = u == 0 ? 5 : u < 6 ? u - 1 : u;
        if (c < 5) mbar_wait(sb + B_REL + (c + 1) * 8, 0);
        if (c > 5) mbar_wait(sb + B_E + (c - 6) * 8, 1);
        mbar_expect(sb + B_W + c * 8, 24576);
        #pragma unroll
        for (int j = 0; j < 3; j++) tma3(sb + wslotC(c) + j * 8192, &mp.wo, j * 64, hg, c * 64, sb + B_W + c * 8);
        if (u == 5) {
          await(8 + tg, 4);
          STAMP(18);
          #pragma unroll 1
          for (int k = 0; k < 9; k++) { mbar_expect(sb + B_X + k * 8, 8192); tma2(sb + oslot(k), &mp.o, k * 64, tg * 64, sb + B_X + k * 8); }
        }
      }
      unsigned old;
      asm volatile("atom.add.acq_rel.gpu.global.u32 %0, [%1], 1;" : "=r"(old) : "l"(g_cnt + 64) : "memory");
      if (old == NCTA - 1) {
        #pragma unroll 1
        for (int i = 0; i < 40; i++) g_cnt[i * 32] = 0;
        g_cnt[1] = 0; g_cnt[2] = 0;
      }
    }
  } else {
    asm volatile("setmaxnreg.inc.sync.aligned.u32 112;");
    const int warp = (threadIdx.x >> 5) & 3, lane = threadIdx.x & 31, g = lane >> 2, t = lane & 3;
    uint32_t* sq = (uint32_t*)(smem + S_Q) + (warp * 16 + g) * QP;
    if (wg == 0) {
      gemm<false, 0>(sb, sq + t);
      STAMP0(4);
    } else if (wg == 1) {
      gemm<false, 1>(sb, sq + t);
    } else if (wg == 3) {
      special(smem, sb, tg * 64 + hg * 16, hg * 16);
      if (threadIdx.x == 384) STAMP(2);
      bar_arrive(3, 416);
    }
    bar_sync(6, 512);
    STAMP0(7);
    volatile uint32_t* stash = (volatile uint32_t*)(smem + S_FLAG) + threadIdx.x;
    volatile uint8_t* fl = smem + S_FLAG - 512 + threadIdx.x;
    const uint32_t sb16 = sb >> 4;
    const int q0 = tg * 64 + warp * 16;
    uint32_t qa[8];
    stash[0] = 0; qa[6] = stash[0]; qa[7] = stash[0];
    {
      const float QS = 0.23570226f * 1.44269504f;
      float n[2][2];
      uint32_t qh[2];
      #pragma unroll
      for (int i = 1; i >= 0; i--) {
        const uint32_t* qp = sq + (i * 4 + wg) * 9;
        uint32_t raw[6] = {qp[t], qp[8 * QP + t], qp[t + 4], qp[8 * QP + t + 4], t == 0 ? qp[8] : 0u, t == 0 ? qp[8 * QP + 8] : 0u};
        n[i][0] = n[i][1] = 0.f;
        #pragma unroll
        for (int j = 0; j < 6; j++) {
          float a = bflo(raw[j]), b = bfhi(raw[j]);
          n[i][j & 1] += a * a + b * b;
          qa[j] = pack2h(a * (QS / 32.f), b * (QS / 32.f));
        }
        #pragma unroll
        for (int r = 0; r < 2; r++) {
          n[i][r] += __shfl_xor_sync(~0u, n[i][r], 1); n[i][r] += __shfl_xor_sync(~0u, n[i][r], 2);
          n[i][r] = n[i][r] <= 65536.f ? sqrta(n[i][r]) : INFINITY;
        }
        if (i) {
          #pragma unroll
          for (int j = 0; j < 4; j++) stash[j * 512] = qa[j];
          qh[0] = qa[4]; qh[1] = qa[5];
        }
      }
      bar_sync(4, 544);
      const float2 st = *(const float2*)(smem + S_ST);
      const bool kvbad = !(st.x <= 65536.f) || !(st.y <= 16384.f) || !(st.y >= 0.015625f);
      const float kn = sqrta(st.x) * (QS * 1.01f * 8.f);
      uint32_t flags = 0;
      #pragma unroll
      for (int i = 0; i < 2; i++) {
        #pragma unroll
        for (int r = 0; r < 2; r++) {
          float M = ceilf(n[i][r] * kn) * 0.125f;
          if (kvbad || !(M <= 40.f)) { flags |= 1u << (3 * i); M = 0.f; }
          if (M > 14.f) { flags |= 2u << (3 * i + r); M = 28.f - M; }
          if (t == 1) (i ? qh[r] : qa[4 + r]) = pack2h(M, M - 13.f);
        }
      }
      stash[4 * 512] = qh[0]; stash[5 * 512] = qh[1];
      *fl = flags;
    }
    uint32_t s0[16], s1[16], p0[16], p1[16];
    STAMP0(14);
    mbar_wait(sb + B_KV, 0);
    STAMP0(19);
    wg_fence(); qk64(s0, qa, sb16); wg_commit();
    #pragma unroll
    for (int i = 0; i < 2; i++) {
      float o[12];
      #pragma unroll
      for (int k = 0; k < 12; k++) asm volatile("mov.b32 %0, 0;" : "=f"(o[k]));
      wg_wait<0>(); fence_regs<16>(s0);
      STAMP0(9 + 3 * i);
      #pragma unroll 1
      for (int c = 0; c < 8; c++) {
        const uint32_t a0 = sb16 + c * (CH >> 4), an = c == 7 ? sb16 : a0 + (CH >> 4);
        wg_fence(); qk64(s1, qa, a0 + 64); wg_commit();
        softmax64(s0, p0); fence_regs<16>(p0);
        wg_fence(); pv64(o, p0, a0); PVC qk64(s0, qa, a0 + 128); wg_commit();
        wg_wait<WN>(); fence_regs<16>(s1);
        if (i == 1 && lane == 0 && c) mbar_arrive(sb + B_REL + 8 * c - 8);
        softmax64(s1, p1); fence_regs<16>(p1);
        wg_fence(); pv64(o, p1, a0 + 64); PVC qk64(s1, qa, a0 + 192); wg_commit();
        wg_wait<WN>(); fence_regs<16>(s0);
        softmax64(s0, p0); fence_regs<16>(p0);
        if (i == 0 && c < 7) mbar_wait(sb + B_KV + 8 * c + 8, 0);
        wg_fence(); pv64(o, p0, a0 + 128); PVC qk64(s0, qa, an); wg_commit();
        wg_wait<WN>(); fence_regs<16>(s1);
        softmax64(s1, p1); fence_regs<16>(p1);
        wg_fence(); pv64(o, p1, a0 + 192); wg_commit();
        wg_wait<1>(); fence_regs<16>(s0);
      }
      wg_wait<0>();
      fence_regs<12>(o);
      RETID
      if (i == 0) {
        #pragma unroll
        for (int j = 0; j < 6; j++) qa[j] = stash[j * 512];
        stash[0] = 0; qa[6] = stash[0]; qa[7] = stash[0];
        wg_fence(); qk64(s0, qa, sb16); wg_commit();
      }
      STAMP0(10 + 3 * i);
      const uint32_t flags = *fl;
      float l0 = __shfl_sync(0xffffffffu, o[0], lane | 3), l1 = __shfl_sync(0xffffffffu, o[2], lane | 3);
      bool bad = ((flags >> (3 * i)) & 1) || !(l0 <= 3e38f) || !(l1 <= 3e38f) || !(l0 > 0.f) || !(l1 > 0.f)
                 || (((flags >> (3 * i + 1)) & 1) && l0 < 256.f) || (((flags >> (3 * i + 2)) & 1) && l1 < 256.f);
      if (__any_sync(0xffffffffu, bad)) *fl = flags | (64u << i);
      else {
        float r0 = __fdividef(1.f, l0), r1 = __fdividef(1.f, l1);
        uint32_t* op0 = (uint32_t*)(g_o + (size_t)(q0 + g) * DM + (hg * 8 + i * 4 + wg) * 18);
        uint32_t* op1 = op0 + 4 * DM;
        op0[t] = pack2(o[4] * r0, o[5] * r0); op1[t] = pack2(o[6] * r1, o[7] * r1);
        op0[t + 4] = pack2(o[8] * r0, o[9] * r0); op1[t + 4] = pack2(o[10] * r1, o[11] * r1);
        if (t == 2) { op0[8] = pack2(o[0] * r0, o[1] * r0); op1[8] = pack2(o[2] * r1, o[3] * r1); }
      }
    }
    {
    RETID
    uint32_t* sq2 = (uint32_t*)(smem + S_Q) + (warp * 16 + g) * QP;
    {
      const uint32_t flags = *fl;
      if (flags >> 6) await(3, NCTA);
      #pragma unroll 1
      for (int i = 0; i < 2; i++)
        if ((flags >> (6 + i)) & 1) attn_exact((const __nv_bfloat16*)(smem + S_Q) + warp * 32 * QP + (i * 4 + wg) * 18, q0, hg * 8 + i * 4 + wg, lane);
    }
    if ((tx_ & 127) == 0 && wg) STAMP(14 + wg);
    bar_sync(6, 512);
    if (tx_ == 384) signal(8 + tg);
    uint4 xr[3];
    #pragma unroll
    for (int u = 0; u < 3; u++) {
      const int v = tx_ + u * 512, row = v / 18, c8 = v % 18;
      if (v < 1152) xr[u] = ldg16(x + (size_t)(tg * 64 + row) * DM + hg * 144 + c8 * 8);
    }
    if (wg == 0) gemm<true, 0>(sb, sq2 + t);
    if (wg == 1) gemm<true, 1>(sb, sq2 + t);
    STAMP0(20);
    bar_sync(5, 640);
    const int li = *(const int*)(smem + S_ST + 12) - tg * 64;
    #pragma unroll
    for (int u = 0; u < 3; u++) {
      const int v = tx_ + u * 512, row = v / 18, c8 = v % 18;
      if (v < 1152) {
        const float gg = ((const float*)(smem + S_G))[row];
        const uint4 av = *(const uint4*)(smem + S_Q + row * (QP * 4) + c8 * 16);
        const uint32_t aa[4] = {av.x, av.y, av.z, av.w}, xx[4] = {xr[u].x, xr[u].y, xr[u].z, xr[u].w};
        uint32_t r[4];
        #pragma unroll
        for (int k = 0; k < 4; k++) {
          float b0 = bflo(xx[k]), b1 = bfhi(xx[k]);
          if (row == li) { const float* ys = (const float*)(smem + S_Y) + c8 * 8 + 2 * k; b0 += ys[0]; b1 += ys[1]; }
          r[k] = pack2(fmaf(gg, bflo(aa[k]) - b0, b0), fmaf(gg, bfhi(aa[k]) - b1, b1));
        }
        *(uint4*)(out + (size_t)(tg * 64 + row) * DM + hg * 144 + c8 * 8) = make_uint4(r[0], r[1], r[2], r[3]);
      }
    }
    }
    STAMP0(21);
  }
}

typedef CUresult (*EncFn)(CUtensorMap*, CUtensorMapDataType, cuuint32_t, void*, const cuuint64_t*, const cuuint64_t*, const cuuint32_t*, const cuuint32_t*,
                          CUtensorMapInterleave, CUtensorMapSwizzle, CUtensorMapL2promotion, CUtensorMapFloatOOBfill);
static void make_map(EncFn enc, CUtensorMap* m, const void* base, int cols, int rows, bool grouped) {
  cuuint64_t d2[2] = {(cuuint64_t)cols, (cuuint64_t)rows}, s2[1] = {(cuuint64_t)cols * 2}, d3[3] = {144, 4, (cuuint64_t)rows}, s3[2] = {288, (cuuint64_t)cols * 2};
  cuuint32_t b2[2] = {64, 64}, b3[3] = {64, 1, 64}, es[3] = {1, 1, 1};
  enc(m, CU_TENSOR_MAP_DATA_TYPE_BFLOAT16, grouped ? 3 : 2, (void*)base, grouped ? d3 : d2, grouped ? s3 : s2, grouped ? b3 : b2, es, CU_TENSOR_MAP_INTERLEAVE_NONE,
      CU_TENSOR_MAP_SWIZZLE_128B, CU_TENSOR_MAP_L2_PROMOTION_L2_256B, CU_TENSOR_MAP_FLOAT_OOB_FILL_NONE);
}

extern "C" void kernel_launch(void* const* d_in, const int* in_sizes, int n_in, void* d_out, int out_size) {
  typedef const __nv_bfloat16* P;
  static EncFn enc = nullptr;
  static void* po = nullptr;
  if (!enc) {
    cudaDriverEntryPointQueryResult qr;
    cudaGetDriverEntryPoint("cuTensorMapEncodeTiled", (void**)&enc, cudaEnableDefault, &qr);
    cudaGetSymbolAddress(&po, g_o);
    cudaFuncSetAttribute(k_fused, cudaFuncAttributeMaxDynamicSharedMemorySize, SMEM);
  }
  Maps mp;
  make_map(enc, &mp.x, d_in[0], DM, SEQ, false); make_map(enc, &mp.wq, d_in[1], DM, DM, true); make_map(enc, &mp.wo, d_in[4], DM, DM, true);
  make_map(enc, &mp.o, po, DM, SEQ, false); make_map(enc, &mp.wg, d_in[7], FF, DM, false); make_map(enc, &mp.wu, d_in[8], FF, DM, false);
  make_map(enc, &mp.wd, d_in[9], DM, FF, false);
  k_fused<<<NCTA, 640, SMEM, cudaStreamPerThread>>>(mp, (P)d_in[0], (P)d_in[2], (P)d_in[3], (P)d_in[6], (P)d_in[10], (__nv_bfloat16*)d_out);
}
```

```cpp
#include <cuda_runtime.h>
#include <cuda_bf16.h>
#include <cuda_fp16.h>
#include <stdint.h>
#include <cuda.h>

constexpr int SEQ = 2048, DM = 576, FF = 4608, NSL = 72, NCTA = 128;
constexpr uint32_t KMASK = 0x25;

__device__ __align__(128) __nv_bfloat16 g_o[SEQ * DM];
__device__ uint4 g_kv[5 * SEQ];
__device__ float g_kraw[SEQ * 18];
__device__ float g_vraw[SEQ * 18];
__device__ float g_gate[SEQ];
__device__ float4 g_stat[NCTA];
__device__ float g_ypart[NSL * DM];
__device__ __align__(128) unsigned g_cnt[40 * 32];

#define STAMP(k)
#define STAMP0(k)
__device__ __forceinline__ void wgh_n64_sd0(uint32_t* d, uint32_t a0, uint32_t a1, uint32_t a2, uint32_t a3, uint64_t bdesc) {
  asm volatile("{\n.reg .pred p;\nsetp.ne.b32 p, 0, 0;\n"
    "wgmma.mma_async.sync.aligned.m64n64k16.f16.f16.f16 {%0, %1, %2, %3, %4, %5, %6, %7, %8, %9, %10, %11, %12, %13, %14, %15}, {%16, %17, %18, %19}, %20, p, 1, 1, 0;\n}\n"
    : "=r"(d[0]), "=r"(d[1]), "=r"(d[2]), "=r"(d[3]), "=r"(d[4]), "=r"(d[5]), "=r"(d[6]), "=r"(d[7]), "=r"(d[8]), "=r"(d[9]), "=r"(d[10]), "=r"(d[11]), "=r"(d[12]), "=r"(d[13]), "=r"(d[14]), "=r"(d[15]) : "r"(a0), "r"(a1), "r"(a2), "r"(a3), "l"(bdesc));
}
__device__ __forceinline__ void wgh_n64_sd1(uint32_t* d, uint32_t a0, uint32_t a1, uint32_t a2, uint32_t a3, uint64_t bdesc) {
  asm volatile("{\n.reg .pred p;\nsetp.ne.b32 p, 1, 0;\n"
    "wgmma.mma_async.sync.aligned.m64n64k16.f16.f16.f16 {%0, %1, %2, %3, %4, %5, %6, %7, %8, %9, %10, %11, %12, %13, %14, %15}, {%16, %17, %18, %19}, %20, p, 1, 1, 0;\n}\n"
    : "+r"(d[0]), "+r"(d[1]), "+r"(d[2]), "+r"(d[3]), "+r"(d[4]), "+r"(d[5]), "+r"(d[6]), "+r"(d[7]), "+r"(d[8]), "+r"(d[9]), "+r"(d[10]), "+r"(d[11]), "+r"(d[12]), "+r"(d[13]), "+r"(d[14]), "+r"(d[15]) : "r"(a0), "r"(a1), "r"(a2), "r"(a3), "l"(bdesc));
}
__device__ __forceinline__ void wg_pv(float* d, uint32_t a0, uint32_t a1, uint32_t a2, uint32_t a3, uint64_t bdesc) {
  asm volatile("{\n.reg .pred p;\nsetp.ne.b32 p, 1, 0;\n"
    "wgmma.mma_async.sync.aligned.m64n24k16.f32.f16.f16 {%0, %1, %2, %3, %4, %5, %6, %7, %8, %9, %10, %11}, {%12, %13, %14, %15}, %16, p, 1, 1, 1;\n}\n"
    : "+f"(d[0]), "+f"(d[1]), "+f"(d[2]), "+f"(d[3]), "+f"(d[4]), "+f"(d[5]), "+f"(d[6]), "+f"(d[7]), "+f"(d[8]), "+f"(d[9]), "+f"(d[10]), "+f"(d[11]) : "r"(a0), "r"(a1), "r"(a2), "r"(a3), "l"(bdesc));
}
__device__ __forceinline__ void wg_ss64(float* d, uint64_t adesc, uint64_t bdesc) {
  asm volatile("{\n.reg .pred p;\nsetp.ne.b32 p, 1, 0;\n"
    "wgmma.mma_async.sync.aligned.m64n64k16.f32.bf16.bf16 {%0, %1, %2, %3, %4, %5, %6, %7, %8, %9, %10, %11, %12, %13, %14, %15, %16, %17, %18, %19, %20, %21, %22, %23, %24, %25, %26, %27, %28, %29, %30, %31}, %32, %33, p, 1, 1, 0, 1;\n}\n"
    : "+f"(d[0]), "+f"(d[1]), "+f"(d[2]), "+f"(d[3]), "+f"(d[4]), "+f"(d[5]), "+f"(d[6]), "+f"(d[7]), "+f"(d[8]), "+f"(d[9]), "+f"(d[10]), "+f"(d[11]), "+f"(d[12]), "+f"(d[13]), "+f"(d[14]), "+f"(d[15]), "+f"(d[16]), "+f"(d[17]), "+f"(d[18]), "+f"(d[19]), "+f"(d[20]), "+f"(d[21]), "+f"(d[22]), "+f"(d[23]), "+f"(d[24]), "+f"(d[25]), "+f"(d[26]), "+f"(d[27]), "+f"(d[28]), "+f"(d[29]), "+f"(d[30]), "+f"(d[31]) : "l"(adesc), "l"(bdesc));
}
__device__ __forceinline__ void wg_ss80(float* d, uint64_t adesc, uint64_t bdesc) {
  asm volatile("{\n.reg .pred p;\nsetp.ne.b32 p, 1, 0;\n"
    "wgmma.mma_async.sync.aligned.m64n80k16.f32.bf16.bf16 {%0, %1, %2, %3, %4, %5, %6, %7, %8, %9, %10, %11, %12, %13, %14, %15, %16, %17, %18, %19, %20, %21, %22, %23, %24, %25, %26, %27, %28, %29, %30, %31, %32, %33, %34, %35, %36, %37, %38, %39}, %40, %41, p, 1, 1, 0, 1;\n}\n"
    : "+f"(d[0]), "+f"(d[1]), "+f"(d[2]), "+f"(d[3]), "+f"(d[4]), "+f"(d[5]), "+f"(d[6]), "+f"(d[7]), "+f"(d[8]), "+f"(d[9]), "+f"(d[10]), "+f"(d[11]), "+f"(d[12]), "+f"(d[13]), "+f"(d[14]), "+f"(d[15]), "+f"(d[16]), "+f"(d[17]), "+f"(d[18]), "+f"(d[19]), "+f"(d[20]), "+f"(d[21]), "+f"(d[22]), "+f"(d[23]), "+f"(d[24]), "+f"(d[25]), "+f"(d[26]), "+f"(d[27]), "+f"(d[28]), "+f"(d[29]), "+f"(d[30]), "+f"(d[31]), "+f"(d[32]), "+f"(d[33]), "+f"(d[34]), "+f"(d[35]), "+f"(d[36]), "+f"(d[37]), "+f"(d[38]), "+f"(d[39]) : "l"(adesc), "l"(bdesc));
}
__device__ __forceinline__ void wg_ss8(float* d, uint64_t adesc, uint64_t bdesc) {
  asm volatile("{\n.reg .pred p;\nsetp.ne.b32 p, 1, 0;\n"
    "wgmma.mma_async.sync.aligned.m64n8k16.f32.bf16.bf16 {%0, %1, %2, %3}, %4, %5, p, 1, 1, 1, 0;\n}\n"
    : "+f"(d[0]), "+f"(d[1]), "+f"(d[2]), "+f"(d[3]) : "l"(adesc), "l"(bdesc));
}

__device__ __forceinline__ void wg_fence() { asm volatile("wgmma.fence.sync.aligned;" ::: "memory"); }
__device__ __forceinline__ void wg_commit() { asm volatile("wgmma.commit_group.sync.aligned;" ::: "memory"); }
template<int N> __device__ __forceinline__ void wg_wait() { asm volatile("wgmma.wait_group.sync.aligned %0;" :: "n"(N) : "memory"); }
__device__ __forceinline__ uint32_t pack2(float lo, float hi) { uint32_t r; asm("cvt.rn.bf16x2.f32 %0, %1, %2;" : "=r"(r) : "f"(hi), "f"(lo)); return r; }
__device__ __forceinline__ uint32_t pack2h(float lo, float hi) { uint32_t r; asm("cvt.rn.f16x2.f32 %0, %1, %2;" : "=r"(r) : "f"(hi), "f"(lo)); return r; }
__device__ __forceinline__ float bflo(uint32_t v) { return __uint_as_float(v << 16); }
__device__ __forceinline__ float bfhi(uint32_t v) { return __uint_as_float(v & 0xffff0000u); }
__device__ __forceinline__ float bfr(float v) { return __bfloat162float(__float2bfloat16(v)); }
__device__ __forceinline__ uint32_t hfma2(uint32_t a, uint32_t b, uint32_t c) { uint32_t r; asm("fma.rn.f16x2 %0, %1, %2, %3;" : "=r"(r) : "r"(a), "r"(b), "r"(c)); return r; }
__device__ __forceinline__ uint32_t hfma2r(uint32_t a, uint32_t b, uint32_t c) { uint32_t r; asm("fma.rn.relu.f16x2 %0, %1, %2, %3;" : "=r"(r) : "r"(a), "r"(b), "r"(c)); return r; }
__device__ __forceinline__ uint32_t ex2h2(uint32_t x) { uint32_t r; asm("ex2.approx.f16x2 %0, %1;" : "=r"(r) : "r"(x)); return r; }
__device__ __forceinline__ uint64_t mk64(uint32_t lo, uint32_t hi) { uint64_t d; asm("mov.b64 %0, {%1, %2};" : "=l"(d) : "r"(lo), "r"(hi)); return d; }
template<int N> __device__ __forceinline__ void fence_regs(float* r) {
  #pragma unroll
  for (int i = 0; i < N; i++) asm volatile("" : "+f"(r[i]) :: "memory");
}
template<int N> __device__ __forceinline__ void fence_regs(uint32_t* r) {
  #pragma unroll
  for (int i = 0; i < N; i++) asm volatile("" : "+r"(r[i]) :: "memory");
}
__device__ __forceinline__ void cp16(uint32_t dst, const void* src) { asm volatile("cp.async.cg.shared.global [%0], [%1], 16;" :: "r"(dst), "l"(src) : "memory"); }
__device__ __forceinline__ void cp4(uint32_t dst, const void* src) { asm volatile("cp.async.ca.shared.global [%0], [%1], 4;" :: "r"(dst), "l"(src) : "memory"); }
__device__ __forceinline__ void cp_commit() { asm volatile("cp.async.commit_group;" ::: "memory"); }
template<int N> __device__ __forceinline__ void cp_wait() { asm volatile("cp.async.wait_group %0;" :: "n"(N) : "memory"); }
__device__ __forceinline__ void proxy_fence() { asm volatile("fence.proxy.async.shared::cta;" ::: "memory"); }
__device__ __forceinline__ void pdl_wait() { asm volatile("griddepcontrol.wait;" ::: "memory"); }
__device__ __forceinline__ void pdl_go() { asm volatile("griddepcontrol.launch_dependents;" ::: "memory"); }
__device__ __forceinline__ uint4 ldg16(const void* p) { uint4 v; asm volatile("ld.global.nc.L1::no_allocate.v4.u32 {%0,%1,%2,%3}, [%4];" : "=r"(v.x), "=r"(v.y), "=r"(v.z), "=r"(v.w) : "l"(p)); return v; }
__device__ __forceinline__ uint4 ldg16c(const void* p) { uint4 v; asm volatile("ld.global.L1::no_allocate.v4.u32 {%0,%1,%2,%3}, [%4];" : "=r"(v.x), "=r"(v.y), "=r"(v.z), "=r"(v.w) : "l"(p) : "memory"); return v; }
__device__ __forceinline__ void mbar_wait(uint32_t bar, uint32_t parity) {
  #pragma unroll 1
  for (int it = 0; it < (1 << 22); it++) {
    uint32_t ok;
    asm volatile("{\n.reg .pred p;\nmbarrier.try_wait.parity.shared::cta.b64 p, [%1], %2;\nselp.u32 %0, 1, 0, p;\n}\n" : "=r"(ok) : "r"(bar), "r"(parity) : "memory");
    if (ok) break;
  }
}
__device__ __forceinline__ void mbar_init(uint32_t bar, uint32_t cnt) { asm volatile("mbarrier.init.shared::cta.b64 [%0], %1;" :: "r"(bar), "r"(cnt) : "memory"); }
__device__ __forceinline__ void mbar_expect(uint32_t bar, uint32_t bytes) { asm volatile("mbarrier.arrive.expect_tx.shared::cta.b64 _, [%0], %1;" :: "r"(bar), "r"(bytes) : "memory"); }
__device__ __forceinline__ void mbar_arrive(uint32_t bar) { asm volatile("mbarrier.arrive.shared::cta.b64 _, [%0];" :: "r"(bar) : "memory"); }
__device__ __forceinline__ void tma2(uint32_t dst, const CUtensorMap* m, int c0, int c1, uint32_t bar) {
  asm volatile("cp.async.bulk.tensor.2d.shared::cluster.global.mbarrier::complete_tx::bytes [%0], [%1, {%3, %4}], [%2];" :: "r"(dst), "l"(m), "r"(bar), "r"(c0), "r"(c1) : "memory");
}
__device__ __forceinline__ void tma3(uint32_t dst, const CUtensorMap* m, int c0, int c1, int c2, uint32_t bar) {
  asm volatile("cp.async.bulk.tensor.3d.shared::cluster.global.mbarrier::complete_tx::bytes [%0], [%1, {%3, %4, %5}], [%2];" :: "r"(dst), "l"(m), "r"(bar), "r"(c0), "r"(c1), "r"(c2) : "memory");
}
__device__ __forceinline__ void bulk(uint32_t dst, const void* src, uint32_t bytes, uint32_t bar) {
  asm volatile("cp.async.bulk.shared::cluster.global.mbarrier::complete_tx::bytes [%0], [%1], %2, [%3];" :: "r"(dst), "l"(src), "r"(bytes), "r"(bar) : "memory");
}
__device__ __forceinline__ void bar_sync(int id, int n) { asm volatile("bar.sync %0, %1;" :: "r"(id), "r"(n) : "memory"); }
__device__ __forceinline__ void bar_arrive(int id, int n) { asm volatile("bar.arrive %0, %1;" :: "r"(id), "r"(n) : "memory"); }
__device__ __forceinline__ void proxy_fence_all() { asm volatile("fence.proxy.async;" ::: "memory"); }
__device__ __forceinline__ void signal(int i) {
  asm volatile("fence.acq_rel.gpu;\nred.relaxed.gpu.global.add.u32 [%0], 1;" :: "l"(g_cnt + i * 32) : "memory");
}
__device__ __forceinline__ void await(int i, unsigned n) {
  #pragma unroll 1
  for (int it = 0; it < (1 << 21); it++) {
    unsigned v; asm volatile("ld.acquire.gpu.global.u32 %0, [%1];" : "=r"(v) : "l"(g_cnt + i * 32) : "memory");
    if (v >= n) break;
  }
  proxy_fence_all();
}
__device__ __forceinline__ void ldsm4(uint32_t a, uint32_t* r) {
  asm volatile("ldmatrix.sync.aligned.m8n8.x4.shared.b16 {%0,%1,%2,%3}, [%4];" : "=r"(r[0]), "=r"(r[1]), "=r"(r[2]), "=r"(r[3]) : "r"(a) : "memory");
}
__device__ __forceinline__ void mma16(float* d, const uint32_t* a, uint32_t b0, uint32_t b1) {
  asm volatile("mma.sync.aligned.m16n8k16.row.col.f32.bf16.bf16.f32 {%0,%1,%2,%3}, {%4,%5,%6,%7}, {%8,%9}, {%0,%1,%2,%3};"
    : "+f"(d[0]), "+f"(d[1]), "+f"(d[2]), "+f"(d[3]) : "r"(a[0]), "r"(a[1]), "r"(a[2]), "r"(a[3]), "r"(b0), "r"(b1));
}

constexpr uint32_t KB = 1024, CH = 20480;
constexpr uint32_t S_X = 44 * KB, S_W = 116 * KB;
constexpr uint32_t S_FFN = 160 * KB, S_Q = 192 * KB, S_FLAG = 212 * KB, S_BAR = 224 * KB;
constexpr uint32_t B_X = S_BAR, B_W = B_X + 72, B_E = B_W + 72, B_R = B_E + 40, B_KV = B_R + 8, B_REL = B_KV + 64, B_F = B_REL + 56;
constexpr uint32_t S_ST = S_BAR + 352, S_G = S_BAR + 384, S_Y = S_G + 256, S_H = S_Y + 576, S_XS = S_H + 128, SMEM = S_XS + 1152 + 128;
constexpr int QP = 76;
__device__ __forceinline__ uint32_t wslotA(int c) { return S_W + (c & 3) * 24 * KB; }
__device__ __forceinline__ uint32_t wslotC(int c) { return c == 5 ? S_FFN : (c < 5 ? c : c - 6) * 24 * KB; }
__device__ __forceinline__ uint32_t oslot(int c) { return (c < 5 ? 120 + 8 * c : 152 + 8 * c) * KB; }

template<bool C, int W> __device__ __forceinline__ void gemm(uint32_t sb, uint32_t* sq) {
  constexpr int NA = W ? 40 : 32;
  float acc[NA];
  #pragma unroll
  for (int i = 0; i < NA; i++) asm volatile("mov.b32 %0, 0;" : "=f"(acc[i]));
  const uint32_t hi = 64u | (1u << 30);
  #pragma unroll
  for (int c = 0; c < 9; c++) {
    const uint32_t alo = ((sb + (C ? oslot(c) : S_X + c * 8192)) >> 4) | (1u << 16), blo = ((sb + (C ? wslotC(c) : wslotA(c)) + W * 8192) >> 4) | (512u << 16);
    mbar_wait(sb + B_X + c * 8, C);
    mbar_wait(sb + B_W + c * 8, C);
    wg_fence();
    #pragma unroll
    for (int k = 0; k < 4; k++) { if (W) wg_ss80(acc, mk64(alo + k * 2, hi), mk64(blo + k * 128, hi)); else wg_ss64(acc, mk64(alo + k * 2, hi), mk64(blo + k * 128, hi)); }
    wg_commit();
    if (c >= 1 && c <= (C ? 3 : 5)) { wg_wait<1>(); if ((threadIdx.x & 31) == 0) mbar_arrive(sb + B_E + (c - 1) * 8); }
  }
  wg_wait<0>();
  fence_regs<NA>(acc);
  if (!C && !W) STAMP0(22);
  if (!C) bar_arrive(3, 416);
  bar_sync(7, 256);
  #pragma unroll
  for (int j = 0; j < NA / 4; j++) { sq[W * 32 + j * 4] = pack2(acc[4*j], acc[4*j+1]); sq[8 * QP + W * 32 + j * 4] = pack2(acc[4*j+2], acc[4*j+3]); }
}

__device__ __forceinline__ void special(uint8_t* smem, uint32_t sb, int tok0, int row0) {
  const int tid = threadIdx.x & 127, warp = tid >> 5, lane = tid & 31, g = lane >> 2, t = lane & 3;
  float acc[6][4];
  #pragma unroll
  for (int i = 0; i < 6; i++) { acc[i][0] = acc[i][1] = acc[i][2] = acc[i][3] = 0.f; }
  const uint32_t* raw = (const uint32_t*)smem;
  const int r = row0 + (lane & 15);
  const uint32_t xa = sb + S_X + r * 128 + (((warp * 2 + (lane >> 4)) ^ (r & 7)) << 4);
  const int kb = warp * 16 + 2 * t;
  const uint32_t* pk = raw + kb * 9 + g;
  const uint32_t* pl = g < 2 ? raw + g * 5184 + kb * 9 + 8 : raw + 10368 + (g & 1) * 288 + (kb >> 1);
  const int ls = g < 2 ? 9 : 0, lc = g < 2 ? 576 : 32, l8 = g < 2 ? 72 : 4;
  const uint32_t se = g < 2 ? 0x5410 : 0x3210;
  mbar_wait(sb + B_R, 0);
  if (tid == 0) STAMP(1);
  #pragma unroll
  for (int c = 0; c < 9; c++) {
    uint32_t a[4];
    mbar_wait(sb + B_X + c * 8, 0);
    ldsm4(xa + c * 8192, a);
    #pragma unroll
    for (int m = 0; m < 2; m++) {
      const uint32_t* p = pk + m * 5184 + c * 576;
      uint32_t w0 = p[0], w1 = p[9], w2 = p[72], w3 = p[81];
      mma16(acc[2*m], a, __byte_perm(w0, w1, 0x5410), __byte_perm(w2, w3, 0x5410));
      mma16(acc[2*m+1], a, __byte_perm(w0, w1, 0x7632), __byte_perm(w2, w3, 0x7632));
    }
    const uint32_t* p = pl + c * lc;
    uint32_t w0 = p[0], w1 = p[ls], w2 = p[l8], w3 = p[l8 + ls];
    mma16(acc[4], a, __byte_perm(w0, w1, se), __byte_perm(w2, w3, se));
    mma16(acc[5], a, __byte_perm(w0, w1, 0x7632), __byte_perm(w2, w3, 0x7632));
  }
  if (tid == 0) STAMP(6);
  float* part = (float*)(smem + S_FLAG);
  #pragma unroll
  for (int h = 0; h < 2; h++) {
    float* q = part + (warp * 16 + g + h * 8) * 44;
    *(float4*)(q + 4 * t) = make_float4(acc[0][2*h], acc[1][2*h], acc[0][2*h+1], acc[1][2*h+1]);
    *(float4*)(q + 16 + 4 * t) = make_float4(acc[2][2*h], acc[3][2*h], acc[2][2*h+1], acc[3][2*h+1]);
    if (t < 2) *(float2*)(q + 32 + 2 * t) = make_float2(acc[4][2*h], acc[4][2*h+1]);
    if (t == 0) *(float2*)(q + 36) = make_float2(acc[5][2*h], acc[5][2*h+1]);
  }
  bar_sync(2, 128);
  #pragma unroll
  for (int i = tid; i < 176; i += 128) {
    float4 a = ((float4*)part)[i], b = ((float4*)part)[i + 176], c = ((float4*)part)[i + 352], d = ((float4*)part)[i + 528];
    ((float4*)part)[i] = make_float4((a.x + b.x) + (c.x + d.x), (a.y + b.y) + (c.y + d.y), (a.z + b.z) + (c.z + d.z), (a.w + b.w) + (c.w + d.w));
  }
  bar_sync(2, 128);
  if (warp == 0) {
    const int isv = lane >> 4, key = tok0 + (lane & 15);
    const float* q = part + (lane & 15) * 44;
    float v[18];
    #pragma unroll
    for (int d = 0; d < 16; d++) v[d] = bfr(q[isv * 16 + d]);
    v[16] = bfr(q[32 + isv]); v[17] = bfr(q[36 + isv]);
    const bool mufu = (KMASK >> ((key >> 3) & 7)) & 1;
    const float sc = isv ? 1.f : mufu ? 32.f : 0.0625f;
    uint4* kv = g_kv + (key >> 8) * 1280 + (key & 255) + isv * 768;
    kv[0] = make_uint4(pack2h(v[0] * sc, v[1] * sc), pack2h(v[2] * sc, v[3] * sc), pack2h(v[4] * sc, v[5] * sc), pack2h(v[6] * sc, v[7] * sc));
    kv[256] = make_uint4(pack2h(v[8] * sc, v[9] * sc), pack2h(v[10] * sc, v[11] * sc), pack2h(v[12] * sc, v[13] * sc), pack2h(v[14] * sc, v[15] * sc));
    ((uint2*)(kv + 512 - isv * 768))[isv] = make_uint2(pack2h(v[16] * sc, v[17] * sc), isv ? 0x00003C00u : mufu ? 0x3C000000u : 0x00001800u);
    float s = 0.f, z = 0.f;
    #pragma unroll
    for (int d = 0; d < 18; d++) { s = isv ? fmaxf(s, fabsf(v[d])) : fmaf(v[d], v[d], s); z = fmaf(v[d], 0.f, z); }
    s += z;
    if (!(s <= 3e38f)) s = 3e38f;
    if (isv) g_gate[key] = __fdividef(1.f, 1.f + __expf(-bfr(q[35])));
    float rr = q[34]; int ri = key;
    #pragma unroll
    for (int o = 8; o; o >>= 1) {
      s = fmaxf(s, __shfl_xor_sync(~0u, s, o));
      float r2 = __shfl_xor_sync(~0u, rr, o); int i2 = __shfl_xor_sync(~0u, ri, o);
      if (r2 > rr || (r2 == rr && i2 < ri)) { rr = r2; ri = i2; }
    }
    const float vm = __shfl_xor_sync(~0u, s, 16);
    if (lane == 0) { g_stat[blockIdx.x] = make_float4(s, vm, rr, __int_as_float(ri)); atomicMax(g_cnt + 1, __float_as_uint(s)); atomicMax(g_cnt + 2, __float_as_uint(vm)); }
    __syncwarp();
    if (lane == 0) STAMP(8);
    if (lane == 0) signal(0);
    #pragma unroll
    for (int d = 0; d < 18; d++) (isv ? g_vraw : g_kraw)[d * SEQ + key] = v[d];
  }
}
__device__ __forceinline__ bool elect() { uint32_t p; asm volatile("{\n.reg .pred q;\nelect.sync _|q, 0xffffffff;\nselp.u32 %0, 1, 0, q;\n}" : "=r"(p)); return p; }
__device__ __forceinline__ float sqrta(float x) { float r; asm("sqrt.approx.f32 %0, %1;" : "=f"(r) : "f"(x)); return r; }
__device__ __forceinline__ uint32_t ex2poly(uint32_t x) {
  uint32_t t = hfma2r(x, 0x02000200u, 0u);
  uint32_t u = hfma2(t, 0xF800F800u, x);
  uint32_t e = hfma2r(u, 0x47AC47ACu, 0x29A029A0u);
  uint32_t p = hfma2(e, u, 0x08000800u);
  return p + __funnelshift_l(t, t, 10);
}
__device__ __forceinline__ void softmax64(const uint32_t* s, uint32_t* p) {
  #pragma unroll
  for (int j = 0; j < 8; j++) {
    if ((KMASK >> j) & 1) { p[2*j] = ex2h2(s[2*j]); p[2*j+1] = ex2h2(s[2*j+1]); }
    else { p[2*j] = ex2poly(s[2*j]); p[2*j+1] = ex2poly(s[2*j+1]); }
  }
}
__device__ __forceinline__ uint32_t kvt(int j) { return (j >> 2) * (CH >> 4) + (j & 3) * 64; }
__device__ __forceinline__ void qk64(uint32_t* s, const uint32_t* q, uint32_t a16) {
  uint32_t lo = a16 | (256u << 16);
  wgh_n64_sd0(s, q[0], q[1], q[2], q[3], mk64(lo, 8));
  wgh_n64_sd1(s, q[4], q[5], q[6], q[7], mk64(lo + 512, 8));
}
__device__ __forceinline__ void pv64(float* o, const uint32_t* p, uint32_t a16) {
  uint32_t lo = (a16 | (8u << 16)) + 512;
  #pragma unroll
  for (int j = 0; j < 4; j++) wg_pv(o, p[4*j], p[4*j+1], p[4*j+2], p[4*j+3], mk64(lo + j * 16, 256));
}
__device__ __forceinline__ void attn_exact(const __nv_bfloat16* sq, int q0, int h, int lane) {
  #pragma unroll 1
  for (int r = 0; r < 16; r++) {
    float q[18], o[18];
    #pragma unroll
    for (int d = 0; d < 18; d++) { q[d] = __bfloat162float(sq[r * 2 * QP + d]) * 0.23570226f; o[d] = 0.f; }
    float m = -INFINITY;
    #pragma unroll 1
    for (int k = lane; k < SEQ; k += 32) {
      float s = 0.f;
      #pragma unroll
      for (int d = 0; d < 18; d++) s = fmaf(q[d], __ldcg(g_kraw + d * SEQ + k), s);
      m = fmaxf(m, s);
    }
    #pragma unroll
    for (int x = 16; x; x >>= 1) m = fmaxf(m, __shfl_xor_sync(~0u, m, x));
    float l = 0.f;
    #pragma unroll 1
    for (int k = lane; k < SEQ; k += 32) {
      float s = 0.f;
      #pragma unroll
      for (int d = 0; d < 18; d++) s = fmaf(q[d], __ldcg(g_kraw + d * SEQ + k), s);
      float p = __expf(s - m);
      l += p;
      #pragma unroll
      for (int d = 0; d < 18; d++) o[d] = fmaf(p, __ldcg(g_vraw + d * SEQ + k), o[d]);
    }
    #pragma unroll
    for (int x = 16; x; x >>= 1) {
      l += __shfl_xor_sync(~0u, l, x);
      #pragma unroll
      for (int d = 0; d < 18; d++) o[d] += __shfl_xor_sync(~0u, o[d], x);
    }
    float inv = __fdividef(1.f, l), mine = 0.f;
    #pragma unroll
    for (int d = 0; d < 18; d++) if (lane == d) mine = o[d];
    if (lane < 18) g_o[(size_t)(q0 + r) * DM + h * 18 + lane] = __float2bfloat16(mine * inv);
  }
}

struct Maps { CUtensorMap x, wq, wo, o, wg, wu, wd; };

__device__ __forceinline__ void ffn_load(uint32_t sb, const Maps& mp, int i) {
  const uint32_t bar = sb + B_F + (i & 3) * 8, dst = sb + S_FFN + (i & 3) * 8192;
  mbar_expect(bar, 8192);
  if (i < 18) tma2(dst, i < 9 ? &mp.wg : &mp.wu, blockIdx.x * 64, (i < 9 ? i : i - 9) * 64, bar);
  else tma2(dst, &mp.wd, (i - 18) * 64, blockIdx.x * 64, bar);
}

#define RETID uint32_t tx_; asm volatile("mov.u32 %0, %%tid.x;" : "=r"(tx_)); const int warp = (tx_ >> 5) & 3, lane = tx_ & 31, g = lane >> 2, t = lane & 3, wg = tx_ >> 7, q0 = tg * 64 + warp * 16; \
  volatile uint32_t* stash = (volatile uint32_t*)(smem + S_FLAG) + tx_; volatile uint8_t* fl = smem + S_FLAG - 512 + tx_; (void)g; (void)t; (void)q0; (void)stash; (void)fl; (void)wg;
#define PVC wg_commit();
#define WN 2
#define WQD 9
#define WQX 6
__global__ void __launch_bounds__(640, 1) k_fused(const __grid_constant__ Maps mp, const __nv_bfloat16* __restrict__ x, const __nv_bfloat16* __restrict__ wk,
    const __nv_bfloat16* __restrict__ wv, const __nv_bfloat16* __restrict__ wr, const __nv_bfloat16* __restrict__ gw, __nv_bfloat16* __restrict__ out) {
  extern __shared__ __align__(1024) uint8_t smem[];
  const uint32_t sb = (uint32_t)__cvta_generic_to_shared(smem);
  const int wg = __shfl_sync(0xffffffffu, threadIdx.x >> 7, 0);
  const int tg = blockIdx.x >> 2, hg = blockIdx.x & 3;
  STAMP0(0);
  if (threadIdx.x == 512) {
    #pragma unroll 1
    for (uint32_t b = B_X; b < B_F + 32; b += 8) mbar_init(sb + b, (b >= B_E && b < B_R) ? 8 : (b >= B_REL && b < B_F) ? 16 : 1);
    asm volatile("fence.mbarrier_init.release.cluster;" ::: "memory");
    proxy_fence();
    mbar_expect(sb + B_R, 43776);
    bulk(sb, wk, 20736, sb + B_R); bulk(sb + 20736, wv, 20736, sb + B_R); bulk(sb + 41472, wr, 1152, sb + B_R); bulk(sb + 42624, gw, 1152, sb + B_R);
    #pragma unroll 1
    for (int c = 0; c < 9; c++) { mbar_expect(sb + B_X + c * 8, 8192); tma2(sb + S_X + c * 8192, &mp.x, c * 64, tg * 64, sb + B_X + c * 8); }
  }
  __syncthreads();
  STAMP0(11);
  if (wg == 4) {
    asm volatile("setmaxnreg.dec.sync.aligned.u32 32;");
    const int tid = threadIdx.x - 512, warp = tid >> 5, lane = tid & 31;
    if (tid == 0) {
      #pragma unroll 1
      for (int c = 0; c < 9; c++) {
        if (c == WQD) mbar_wait(sb + B_X + WQX * 8, 0);
        if (c >= 4) mbar_wait(sb + B_E + (c - 4) * 8, 0);
        mbar_expect(sb + B_W + c * 8, 24576);
        #pragma unroll
        for (int j = 0; j < 3; j++) tma3(sb + wslotA(c) + j * 8192, &mp.wq, j * 64, hg, c * 64, sb + B_W + c * 8);
      }
    } else if (warp == 1) {
      if (lane == 0) {
        uint32_t v0 = 0, v1 = 0, v2 = 0, v3;
        #pragma unroll 1
        for (int it = 0; it < (1 << 21) && v0 < NCTA; it++)
          asm volatile("ld.acquire.gpu.global.v4.u32 {%0,%1,%2,%3}, [%4];" : "=r"(v0), "=r"(v1), "=r"(v2), "=r"(v3) : "l"(g_cnt) : "memory");
        proxy_fence_all();
        STAMP(3);
        #pragma unroll
        for (int c = 0; c < 2; c++) { mbar_expect(sb + B_KV + c * 8, CH); bulk(sb + c * CH, g_kv + c * 1280, CH, sb + B_KV + c * 8); }
        *(uint2*)(smem + S_ST) = make_uint2(v1, v2);
      }
      __syncwarp();
      bar_arrive(4, 544);
      float r = -INFINITY; int ri = 0;
      #pragma unroll
      for (int i = 0; i < 4; i++) {
        float4 s = __ldcg(g_stat + i * 32 + lane);
        if (s.z > r) { r = s.z; ri = __float_as_int(s.w); }
      }
      const float2 gt = __ldcg((const float2*)(g_gate + tg * 64) + lane);
      bar_sync(3, 416);
      if (lane == 0) {
        #pragma unroll 1
        for (int c = 2; c < 8; c++) { mbar_expect(sb + B_KV + c * 8, CH); bulk(sb + c * CH, g_kv + c * 1280, CH, sb + B_KV + c * 8); }
      }
      #pragma unroll
      for (int o = 16; o; o >>= 1) {
        float r2 = __shfl_xor_sync(~0u, r, o); int i2 = __shfl_xor_sync(~0u, ri, o);
        if (r2 > r || (r2 == r && i2 < ri)) { r = r2; ri = i2; }
      }
      if (lane == 0) *(float2*)(smem + S_ST + 8) = make_float2(r, __int_as_float(ri & (SEQ - 1)));
      ((float2*)(smem + S_G))[lane] = gt;
      if (lane == 0) signal(3);
      __syncwarp();
    }
    bar_sync(1, 128);
    const int idx = *(volatile int*)(smem + S_ST + 12);
    if (blockIdx.x < NSL) {
      if (tid == 0) {
        mbar_wait(sb + B_KV + 56, 0);
        #pragma unroll 1
        for (int i = 0; i < 4; i++) ffn_load(sb, mp, i);
      }
      if (tid < 72) *(uint4*)(smem + S_XS + tid * 16) = ldg16(x + (size_t)idx * DM + tid * 8);
      proxy_fence();
      bar_sync(1, 128);
      float acc[4], gt0 = 0.f, gt1 = 0.f;
      #pragma unroll 1
      for (int i = 0; i < 27; i++) {
        if (i == 0 || i == 9 || i >= 18) {
          #pragma unroll
          for (int k = 0; k < 4; k++) asm volatile("mov.b32 %0, 0;" : "=f"(acc[k]));
        }
        const uint32_t alo = ((sb + S_FFN + (i & 3) * 8192) >> 4) | (64u << 16);
        const uint32_t blo = ((sb + (i < 18 ? S_XS + (i < 9 ? i : i - 9) * 128 : S_H)) >> 4) | (1u << 16);
        mbar_wait(sb + B_F + (i & 3) * 8, (i >> 2) & 1);
        wg_fence();
        #pragma unroll
        for (int k = 0; k < 4; k++) wg_ss8(acc, mk64(alo + k * 128, 64u | (1u << 30)), mk64(blo + k * 2, 8));
        wg_commit(); wg_wait<0>(); fence_regs<4>(acc);
        const int row = warp * 16 + (lane >> 2);
        if (i == 8) { gt0 = bfr(acc[0]); gt1 = bfr(acc[2]); }
        if (i == 17) {
          if ((lane & 3) == 0) {
            __nv_bfloat16* hh = (__nv_bfloat16*)(smem + S_H);
            hh[row] = __float2bfloat16(bfr(__fdividef(gt0, 1.f + __expf(-gt0))) * bfr(acc[0]));
            hh[row + 8] = __float2bfloat16(bfr(__fdividef(gt1, 1.f + __expf(-gt1))) * bfr(acc[2]));
          }
          proxy_fence();
        }
        if (i >= 18 && (lane & 3) == 0) { float* yp = g_ypart + blockIdx.x * DM + (i - 18) * 64 + row; yp[0] = acc[0]; yp[8] = acc[2]; }
        bar_sync(1, 128);
        if (tid == 0 && i < 23) ffn_load(sb, mp, i + 4);
      }
      if (tid == 0) { signal(1); STAMP(5); }
    }
    if ((idx >> 6) == tg) {
      if (tid == 0) await(1, NSL);
      bar_sync(1, 128);
      float4* red = (float4*)(smem + S_FFN + 24 * KB);
      if (tid < 108) {
        const float4* yp = (const float4*)(g_ypart + (tid / 36) * 24 * DM + hg * 144) + tid % 36;
        float4 a = make_float4(0.f, 0.f, 0.f, 0.f);
        #pragma unroll 4
        for (int i = 0; i < 24; i++) { float4 b = __ldcg(yp + i * (DM / 4)); a.x += b.x; a.y += b.y; a.z += b.z; a.w += b.w; }
        red[tid] = a;
      }
      bar_sync(1, 128);
      const float rs = bfr(__fdividef(1.f, 1.f + __expf(-bfr(*(volatile float*)(smem + S_ST + 8)))));
      for (int i = tid; i < 144; i += 128) { const float* f = (const float*)red + i; ((float*)(smem + S_Y))[i] = bfr(bfr(f[0] + f[144] + f[288]) * rs); }
    }
    bar_arrive(5, 640);
    if (tid == 0) {
      #pragma unroll 1
      for (int u = 0; u < 9; u++) {
        const int c = u == 0 ? 5 : u < 6 ? u - 1 : u;
        if (c < 5) mbar_wait(sb + B_REL + (c + 1) * 8, 0);
        if (c > 5) mbar_wait(sb + B_E + (c - 6) * 8, 1);
        mbar_expect(sb + B_W + c * 8, 24576);
        #pragma unroll
        for (int j = 0; j < 3; j++) tma3(sb + wslotC(c) + j * 8192, &mp.wo, j * 64, hg, c * 64, sb + B_W + c * 8);
        if (u == 5) {
          await(8 + tg, 4);
          STAMP(18);
          #pragma unroll 1
          for (int k = 0; k < 9; k++) { mbar_expect(sb + B_X + k * 8, 8192); tma2(sb + oslot(k), &mp.o, k * 64, tg * 64, sb + B_X + k * 8); }
        }
      }
      unsigned old;
      asm volatile("atom.add.acq_rel.gpu.global.u32 %0, [%1], 1;" : "=r"(old) : "l"(g_cnt + 64) : "memory");
      if (old == NCTA - 1) {
        #pragma unroll 1
        for (int i = 0; i < 40; i++) g_cnt[i * 32] = 0;
        g_cnt[1] = 0; g_cnt[2] = 0;
      }
    }
  } else {
    asm volatile("setmaxnreg.inc.sync.aligned.u32 112;");
    const int warp = (threadIdx.x >> 5) & 3, lane = threadIdx.x & 31, g = lane >> 2, t = lane & 3;
    uint32_t* sq = (uint32_t*)(smem + S_Q) + (warp * 16 + g) * QP;
    if (wg == 0) {
      gemm<false, 0>(sb, sq + t);
      STAMP0(4);
    } else if (wg == 1) {
      gemm<false, 1>(sb, sq + t);
    } else if (wg == 3) {
      special(smem, sb, tg * 64 + hg * 16, hg * 16);
      if (threadIdx.x == 384) STAMP(2);
      bar_arrive(3, 416);
    }
    bar_sync(6, 512);
    STAMP0(7);
    volatile uint32_t* stash = (volatile uint32_t*)(smem + S_FLAG) + threadIdx.x;
    volatile uint8_t* fl = smem + S_FLAG - 512 + threadIdx.x;
    const uint32_t sb16 = sb >> 4;
    const int q0 = tg * 64 + warp * 16;
    uint32_t qa[8];
    stash[0] = 0; qa[6] = stash[0]; qa[7] = stash[0];
    {
      const float QS = 0.23570226f * 1.44269504f;
      float n[2][2];
      uint32_t qh[2];
      #pragma unroll
      for (int i = 1; i >= 0; i--) {
        const uint32_t* qp = sq + (i * 4 + wg) * 9;
        uint32_t raw[6] = {qp[t], qp[8 * QP + t], qp[t + 4], qp[8 * QP + t + 4], t == 0 ? qp[8] : 0u, t == 0 ? qp[8 * QP + 8] : 0u};
        n[i][0] = n[i][1] = 0.f;
        #pragma unroll
        for (int j = 0; j < 6; j++) {
          float a = bflo(raw[j]), b = bfhi(raw[j]);
          n[i][j & 1] += a * a + b * b;
          qa[j] = pack2h(a * (QS / 32.f), b * (QS / 32.f));
        }
        #pragma unroll
        for (int r = 0; r < 2; r++) {
          n[i][r] += __shfl_xor_sync(~0u, n[i][r], 1); n[i][r] += __shfl_xor_sync(~0u, n[i][r], 2);
          n[i][r] = n[i][r] <= 65536.f ? sqrta(n[i][r]) : INFINITY;
        }
        if (i) {
          #pragma unroll
          for (int j = 0; j < 4; j++) stash[j * 512] = qa[j];
          qh[0] = qa[4]; qh[1] = qa[5];
        }
      }
      bar_sync(4, 544);
      const float2 st = *(const float2*)(smem + S_ST);
      const bool kvbad = !(st.x <= 65536.f) || !(st.y <= 16384.f) || !(st.y >= 0.015625f);
      const float kn = sqrta(st.x) * (QS * 1.01f * 8.f);
      uint32_t flags = 0;
      #pragma unroll
      for (int i = 0; i < 2; i++) {
        #pragma unroll
        for (int r = 0; r < 2; r++) {
          float M = ceilf(n[i][r] * kn) * 0.125f;
          if (kvbad || !(M <= 40.f)) { flags |= 1u << (3 * i); M = 0.f; }
          if (M > 14.f) { flags |= 2u << (3 * i + r); M = 28.f - M; }
          if (t == 1) (i ? qh[r] : qa[4 + r]) = pack2h(M, M - 13.f);
        }
      }
      stash[4 * 512] = qh[0]; stash[5 * 512] = qh[1];
      *fl = flags;
    }
    uint32_t s0[16], s1[16], p0[16], p1[16];
    STAMP0(14);
    mbar_wait(sb + B_KV, 0);
    STAMP0(19);
    wg_fence(); qk64(s0, qa, sb16); wg_commit();
    #pragma unroll
    for (int i = 0; i < 2; i++) {
      float o[12];
      #pragma unroll
      for (int k = 0; k < 12; k++) asm volatile("mov.b32 %0, 0;" : "=f"(o[k]));
      wg_wait<0>(); fence_regs<16>(s0);
      STAMP0(9 + 3 * i);
      #pragma unroll 1
      for (int c = 0; c < 8; c++) {
        const uint32_t a0 = sb16 + c * (CH >> 4), an = c == 7 ? sb16 : a0 + (CH >> 4);
        wg_fence(); qk64(s1, qa, a0 + 64); wg_commit();
        softmax64(s0, p0); fence_regs<16>(p0);
        wg_fence(); pv64(o, p0, a0); PVC qk64(s0, qa, a0 + 128); wg_commit();
        wg_wait<WN>(); fence_regs<16>(s1);
        if (i == 1 && lane == 0 && c) mbar_arrive(sb + B_REL + 8 * c - 8);
        softmax64(s1, p1); fence_regs<16>(p1);
        wg_fence(); pv64(o, p1, a0 + 64); PVC qk64(s1, qa, a0 + 192); wg_commit();
        wg_wait<WN>(); fence_regs<16>(s0);
        softmax64(s0, p0); fence_regs<16>(p0);
        if (i == 0 && c < 7) mbar_wait(sb + B_KV + 8 * c + 8, 0);
        wg_fence(); pv64(o, p0, a0 + 128); PVC qk64(s0, qa, an); wg_commit();
        wg_wait<WN>(); fence_regs<16>(s1);
        softmax64(s1, p1); fence_regs<16>(p1);
        wg_fence(); pv64(o, p1, a0 + 192); wg_commit();
        wg_wait<1>(); fence_regs<16>(s0);
      }
      wg_wait<0>();
      fence_regs<12>(o);
      RETID
      if (i == 0) {
        #pragma unroll
        for (int j = 0; j < 6; j++) qa[j] = stash[j * 512];
        stash[0] = 0; qa[6] = stash[0]; qa[7] = stash[0];
        wg_fence(); qk64(s0, qa, sb16); wg_commit();
      }
      STAMP0(10 + 3 * i);
      const uint32_t flags = *fl;
      float l0 = __shfl_sync(0xffffffffu, o[0], lane | 3), l1 = __shfl_sync(0xffffffffu, o[2], lane | 3);
      bool bad = ((flags >> (3 * i)) & 1) || !(l0 <= 3e38f) || !(l1 <= 3e38f) || !(l0 > 0.f) || !(l1 > 0.f)
                 || (((flags >> (3 * i + 1)) & 1) && l0 < 256.f) || (((flags >> (3 * i + 2)) & 1) && l1 < 256.f);
      if (__any_sync(0xffffffffu, bad)) *fl = flags | (64u << i);
      else {
        float r0 = __fdividef(1.f, l0), r1 = __fdividef(1.f, l1);
        uint32_t* op0 = (uint32_t*)(g_o + (size_t)(q0 + g) * DM + (hg * 8 + i * 4 + wg) * 18);
        uint32_t* op1 = op0 + 4 * DM;
        op0[t] = pack2(o[4] * r0, o[5] * r0); op1[t] = pack2(o[6] * r1, o[7] * r1);
        op0[t + 4] = pack2(o[8] * r0, o[9] * r0); op1[t + 4] = pack2(o[10] * r1, o[11] * r1);
        if (t == 2) { op0[8] = pack2(o[0] * r0, o[1] * r0); op1[8] = pack2(o[2] * r1, o[3] * r1); }
      }
    }
    {
    RETID
    uint32_t* sq2 = (uint32_t*)(smem + S_Q) + (warp * 16 + g) * QP;
    {
      const uint32_t flags = *fl;
      if (flags >> 6) await(3, NCTA);
      #pragma unroll 1
      for (int i = 0; i < 2; i++)
        if ((flags >> (6 + i)) & 1) attn_exact((const __nv_bfloat16*)(smem + S_Q) + warp * 32 * QP + (i * 4 + wg) * 18, q0, hg * 8 + i * 4 + wg, lane);
    }
    if ((tx_ & 127) == 0 && wg) STAMP(14 + wg);
    bar_sync(6, 512);
    if (tx_ == 384) signal(8 + tg);
    uint4 xr[3];
    #pragma unroll
    for (int u = 0; u < 3; u++) {
      const int v = tx_ + u * 512, row = v / 18, c8 = v % 18;
      if (v < 1152) xr[u] = ldg16(x + (size_t)(tg * 64 + row) * DM + hg * 144 + c8 * 8);
    }
    if (wg == 0) gemm<true, 0>(sb, sq2 + t);
    if (wg == 1) gemm<true, 1>(sb, sq2 + t);
    STAMP0(20);
    bar_sync(5, 640);
    const int li = *(const int*)(smem + S_ST + 12) - tg * 64;
    #pragma unroll
    for (int u = 0; u < 3; u++) {
      const int v = tx_ + u * 512, row = v / 18, c8 = v % 18;
      if (v < 1152) {
        const float gg = ((const float*)(smem + S_G))[row];
        const uint4 av = *(const uint4*)(smem + S_Q + row * (QP * 4) + c8 * 16);
        const uint32_t aa[4] = {av.x, av.y, av.z, av.w}, xx[4] = {xr[u].x, xr[u].y, xr[u].z, xr[u].w};
        uint32_t r[4];
        #pragma unroll
        for (int k = 0; k < 4; k++) {
          float b0 = bflo(xx[k]), b1 = bfhi(xx[k]);
          if (row == li) { const float* ys = (const float*)(smem + S_Y) + c8 * 8 + 2 * k; b0 += ys[0]; b1 += ys[1]; }
          r[k] = pack2(fmaf(gg, bflo(aa[k]) - b0, b0), fmaf(gg, bfhi(aa[k]) - b1, b1));
        }
        *(uint4*)(out + (size_t)(tg * 64 + row) * DM + hg * 144 + c8 * 8) = make_uint4(r[0], r[1], r[2], r[3]);
      }
    }
    }
    STAMP0(21);
  }
}

typedef CUresult (*EncFn)(CUtensorMap*, CUtensorMapDataType, cuuint32_t, void*, const cuuint64_t*, const cuuint64_t*, const cuuint32_t*, const cuuint32_t*,
                          CUtensorMapInterleave, CUtensorMapSwizzle, CUtensorMapL2promotion, CUtensorMapFloatOOBfill);
static void make_map(EncFn enc, CUtensorMap* m, const void* base, int cols, int rows, bool grouped) {
  cuuint64_t d2[2] = {(cuuint64_t)cols, (cuuint64_t)rows}, s2[1] = {(cuuint64_t)cols * 2}, d3[3] = {144, 4, (cuuint64_t)rows}, s3[2] = {288, (cuuint64_t)cols * 2};
  cuuint32_t b2[2] = {64, 64}, b3[3] = {64, 1, 64}, es[3] = {1, 1, 1};
  enc(m, CU_TENSOR_MAP_DATA_TYPE_BFLOAT16, grouped ? 3 : 2, (void*)base, grouped ? d3 : d2, grouped ? s3 : s2, grouped ? b3 : b2, es, CU_TENSOR_MAP_INTERLEAVE_NONE,
      CU_TENSOR_MAP_SWIZZLE_128B, CU_TENSOR_MAP_L2_PROMOTION_L2_256B, CU_TENSOR_MAP_FLOAT_OOB_FILL_NONE);
}

extern "C" void kernel_launch(void* const* d_in, const int* in_sizes, int n_in, void* d_out, int out_size) {
  typedef const __nv_bfloat16* P;
  static EncFn enc = nullptr;
  static void* po = nullptr;
  if (!enc) {
    cudaDriverEntryPointQueryResult qr;
    cudaGetDriverEntryPoint("cuTensorMapEncodeTiled", (void**)&enc, cudaEnableDefault, &qr);
    cudaGetSymbolAddress(&po, g_o);
    cudaFuncSetAttribute(k_fused, cudaFuncAttributeMaxDynamicSharedMemorySize, SMEM);
  }
  Maps mp;
  make_map(enc, &mp.x, d_in[0], DM, SEQ, false); make_map(enc, &mp.wq, d_in[1], DM, DM, true); make_map(enc, &mp.wo, d_in[4], DM, DM, true);
  make_map(enc, &mp.o, po, DM, SEQ, false); make_map(enc, &mp.wg, d_in[7], FF, DM, false); make_map(enc, &mp.wu, d_in[8], FF, DM, false);
  make_map(enc, &mp.wd, d_in[9], DM, FF, false);
  k_fused<<<NCTA, 640, SMEM, cudaStreamPerThread>>>(mp, (P)d_in[0], (P)d_in[2], (P)d_in[3], (P)d_in[6], (P)d_in[10], (__nv_bfloat16*)d_out);
}
```

```cpp
#include <cuda_runtime.h>
#include <cuda_bf16.h>
#include <cuda_fp16.h>
#include <stdint.h>
#include <cuda.h>

constexpr int SEQ = 2048, DM = 576, FF = 4608, NSL = 72, NCTA = 128;
constexpr uint32_t KMASK = 0x25;

__device__ __align__(128) __nv_bfloat16 g_o[SEQ * DM];
__device__ uint4 g_kv[5 * SEQ];
__device__ float g_kraw[SEQ * 18];
__device__ float g_vraw[SEQ * 18];
__device__ float g_gate[SEQ];
__device__ float4 g_stat[NCTA];
__device__ float g_ypart[NSL * DM];
__device__ __align__(128) unsigned g_cnt[40 * 32];

#define STAMP(k)
#define STAMP0(k)
__device__ __forceinline__ void wgh_n64_sd0(uint32_t* d, uint32_t a0, uint32_t a1, uint32_t a2, uint32_t a3, uint64_t bdesc) {
  asm volatile("{\n.reg .pred p;\nsetp.ne.b32 p, 0, 0;\n"
    "wgmma.mma_async.sync.aligned.m64n64k16.f16.f16.f16 {%0, %1, %2, %3, %4, %5, %6, %7, %8, %9, %10, %11, %12, %13, %14, %15}, {%16, %17, %18, %19}, %20, p, 1, 1, 0;\n}\n"
    : "=r"(d[0]), "=r"(d[1]), "=r"(d[2]), "=r"(d[3]), "=r"(d[4]), "=r"(d[5]), "=r"(d[6]), "=r"(d[7]), "=r"(d[8]), "=r"(d[9]), "=r"(d[10]), "=r"(d[11]), "=r"(d[12]), "=r"(d[13]), "=r"(d[14]), "=r"(d[15]) : "r"(a0), "r"(a1), "r"(a2), "r"(a3), "l"(bdesc));
}
__device__ __forceinline__ void wgh_n64_sd1(uint32_t* d, uint32_t a0, uint32_t a1, uint32_t a2, uint32_t a3, uint64_t bdesc) {
  asm volatile("{\n.reg .pred p;\nsetp.ne.b32 p, 1, 0;\n"
    "wgmma.mma_async.sync.aligned.m64n64k16.f16.f16.f16 {%0, %1, %2, %3, %4, %5, %6, %7, %8, %9, %10, %11, %12, %13, %14, %15}, {%16, %17, %18, %19}, %20, p, 1, 1, 0;\n}\n"
    : "+r"(d[0]), "+r"(d[1]), "+r"(d[2]), "+r"(d[3]), "+r"(d[4]), "+r"(d[5]), "+r"(d[6]), "+r"(d[7]), "+r"(d[8]), "+r"(d[9]), "+r"(d[10]), "+r"(d[11]), "+r"(d[12]), "+r"(d[13]), "+r"(d[14]), "+r"(d[15]) : "r"(a0), "r"(a1), "r"(a2), "r"(a3), "l"(bdesc));
}
__device__ __forceinline__ void wg_pv(float* d, uint32_t a0, uint32_t a1, uint32_t a2, uint32_t a3, uint64_t bdesc) {
  asm volatile("{\n.reg .pred p;\nsetp.ne.b32 p, 1, 0;\n"
    "wgmma.mma_async.sync.aligned.m64n24k16.f32.f16.f16 {%0, %1, %2, %3, %4, %5, %6, %7, %8, %9, %10, %11}, {%12, %13, %14, %15}, %16, p, 1, 1, 1;\n}\n"
    : "+f"(d[0]), "+f"(d[1]), "+f"(d[2]), "+f"(d[3]), "+f"(d[4]), "+f"(d[5]), "+f"(d[6]), "+f"(d[7]), "+f"(d[8]), "+f"(d[9]), "+f"(d[10]), "+f"(d[11]) : "r"(a0), "r"(a1), "r"(a2), "r"(a3), "l"(bdesc));
}
__device__ __forceinline__ void wg_ss64(float* d, uint64_t adesc, uint64_t bdesc) {
  asm volatile("{\n.reg .pred p;\nsetp.ne.b32 p, 1, 0;\n"
    "wgmma.mma_async.sync.aligned.m64n64k16.f32.bf16.bf16 {%0, %1, %2, %3, %4, %5, %6, %7, %8, %9, %10, %11, %12, %13, %14, %15, %16, %17, %18, %19, %20, %21, %22, %23, %24, %25, %26, %27, %28, %29, %30, %31}, %32, %33, p, 1, 1, 0, 1;\n}\n"
    : "+f"(d[0]), "+f"(d[1]), "+f"(d[2]), "+f"(d[3]), "+f"(d[4]), "+f"(d[5]), "+f"(d[6]), "+f"(d[7]), "+f"(d[8]), "+f"(d[9]), "+f"(d[10]), "+f"(d[11]), "+f"(d[12]), "+f"(d[13]), "+f"(d[14]), "+f"(d[15]), "+f"(d[16]), "+f"(d[17]), "+f"(d[18]), "+f"(d[19]), "+f"(d[20]), "+f"(d[21]), "+f"(d[22]), "+f"(d[23]), "+f"(d[24]), "+f"(d[25]), "+f"(d[26]), "+f"(d[27]), "+f"(d[28]), "+f"(d[29]), "+f"(d[30]), "+f"(d[31]) : "l"(adesc), "l"(bdesc));
}
__device__ __forceinline__ void wg_ss80(float* d, uint64_t adesc, uint64_t bdesc) {
  asm volatile("{\n.reg .pred p;\nsetp.ne.b32 p, 1, 0;\n"
    "wgmma.mma_async.sync.aligned.m64n80k16.f32.bf16.bf16 {%0, %1, %2, %3, %4, %5, %6, %7, %8, %9, %10, %11, %12, %13, %14, %15, %16, %17, %18, %19, %20, %21, %22, %23, %24, %25, %26, %27, %28, %29, %30, %31, %32, %33, %34, %35, %36, %37, %38, %39}, %40, %41, p, 1, 1, 0, 1;\n}\n"
    : "+f"(d[0]), "+f"(d[1]), "+f"(d[2]), "+f"(d[3]), "+f"(d[4]), "+f"(d[5]), "+f"(d[6]), "+f"(d[7]), "+f"(d[8]), "+f"(d[9]), "+f"(d[10]), "+f"(d[11]), "+f"(d[12]), "+f"(d[13]), "+f"(d[14]), "+f"(d[15]), "+f"(d[16]), "+f"(d[17]), "+f"(d[18]), "+f"(d[19]), "+f"(d[20]), "+f"(d[21]), "+f"(d[22]), "+f"(d[23]), "+f"(d[24]), "+f"(d[25]), "+f"(d[26]), "+f"(d[27]), "+f"(d[28]), "+f"(d[29]), "+f"(d[30]), "+f"(d[31]), "+f"(d[32]), "+f"(d[33]), "+f"(d[34]), "+f"(d[35]), "+f"(d[36]), "+f"(d[37]), "+f"(d[38]), "+f"(d[39]) : "l"(adesc), "l"(bdesc));
}
__device__ __forceinline__ void wg_ss8(float* d, uint64_t adesc, uint64_t bdesc) {
  asm volatile("{\n.reg .pred p;\nsetp.ne.b32 p, 1, 0;\n"
    "wgmma.mma_async.sync.aligned.m64n8k16.f32.bf16.bf16 {%0, %1, %2, %3}, %4, %5, p, 1, 1, 1, 0;\n}\n"
    : "+f"(d[0]), "+f"(d[1]), "+f"(d[2]), "+f"(d[3]) : "l"(adesc), "l"(bdesc));
}

__device__ __forceinline__ void wg_fence() { asm volatile("wgmma.fence.sync.aligned;" ::: "memory"); }
__device__ __forceinline__ void wg_commit() { asm volatile("wgmma.commit_group.sync.aligned;" ::: "memory"); }
template<int N> __device__ __forceinline__ void wg_wait() { asm volatile("wgmma.wait_group.sync.aligned %0;" :: "n"(N) : "memory"); }
__device__ __forceinline__ uint32_t pack2(float lo, float hi) { uint32_t r; asm("cvt.rn.bf16x2.f32 %0, %1, %2;" : "=r"(r) : "f"(hi), "f"(lo)); return r; }
__device__ __forceinline__ uint32_t pack2h(float lo, float hi) { uint32_t r; asm("cvt.rn.f16x2.f32 %0, %1, %2;" : "=r"(r) : "f"(hi), "f"(lo)); return r; }
__device__ __forceinline__ float bflo(uint32_t v) { return __uint_as_float(v << 16); }
__device__ __forceinline__ float bfhi(uint32_t v) { return __uint_as_float(v & 0xffff0000u); }
__device__ __forceinline__ float bfr(float v) { return __bfloat162float(__float2bfloat16(v)); }
__device__ __forceinline__ uint32_t hfma2(uint32_t a, uint32_t b, uint32_t c) { uint32_t r; asm("fma.rn.f16x2 %0, %1, %2, %3;" : "=r"(r) : "r"(a), "r"(b), "r"(c)); return r; }
__device__ __forceinline__ uint32_t hfma2r(uint32_t a, uint32_t b, uint32_t c) { uint32_t r; asm("fma.rn.relu.f16x2 %0, %1, %2, %3;" : "=r"(r) : "r"(a), "r"(b), "r"(c)); return r; }
__device__ __forceinline__ uint32_t ex2h2(uint32_t x) { uint32_t r; asm("ex2.approx.f16x2 %0, %1;" : "=r"(r) : "r"(x)); return r; }
__device__ __forceinline__ uint64_t mk64(uint32_t lo, uint32_t hi) { uint64_t d; asm("mov.b64 %0, {%1, %2};" : "=l"(d) : "r"(lo), "r"(hi)); return d; }
template<int N> __device__ __forceinline__ void fence_regs(float* r) {
  #pragma unroll
  for (int i = 0; i < N; i++) asm volatile("" : "+f"(r[i]) :: "memory");
}
template<int N> __device__ __forceinline__ void fence_regs(uint32_t* r) {
  #pragma unroll
  for (int i = 0; i < N; i++) asm volatile("" : "+r"(r[i]) :: "memory");
}
__device__ __forceinline__ void cp16(uint32_t dst, const void* src) { asm volatile("cp.async.cg.shared.global [%0], [%1], 16;" :: "r"(dst), "l"(src) : "memory"); }
__device__ __forceinline__ void cp4(uint32_t dst, const void* src) { asm volatile("cp.async.ca.shared.global [%0], [%1], 4;" :: "r"(dst), "l"(src) : "memory"); }
__device__ __forceinline__ void cp_commit() { asm volatile("cp.async.commit_group;" ::: "memory"); }
template<int N> __device__ __forceinline__ void cp_wait() { asm volatile("cp.async.wait_group %0;" :: "n"(N) : "memory"); }
__device__ __forceinline__ void proxy_fence() { asm volatile("fence.proxy.async.shared::cta;" ::: "memory"); }
__device__ __forceinline__ void pdl_wait() { asm volatile("griddepcontrol.wait;" ::: "memory"); }
__device__ __forceinline__ void pdl_go() { asm volatile("griddepcontrol.launch_dependents;" ::: "memory"); }
__device__ __forceinline__ uint4 ldg16(const void* p) { uint4 v; asm volatile("ld.global.nc.L1::no_allocate.v4.u32 {%0,%1,%2,%3}, [%4];" : "=r"(v.x), "=r"(v.y), "=r"(v.z), "=r"(v.w) : "l"(p)); return v; }
__device__ __forceinline__ uint4 ldg16c(const void* p) { uint4 v; asm volatile("ld.global.L1::no_allocate.v4.u32 {%0,%1,%2,%3}, [%4];" : "=r"(v.x), "=r"(v.y), "=r"(v.z), "=r"(v.w) : "l"(p) : "memory"); return v; }
__device__ __forceinline__ void mbar_wait(uint32_t bar, uint32_t parity) {
  #pragma unroll 1
  for (int it = 0; it < (1 << 22); it++) {
    uint32_t ok;
    asm volatile("{\n.reg .pred p;\nmbarrier.try_wait.parity.shared::cta.b64 p, [%1], %2;\nselp.u32 %0, 1, 0, p;\n}\n" : "=r"(ok) : "r"(bar), "r"(parity) : "memory");
    if (ok) break;
  }
}
__device__ __forceinline__ void mbar_init(uint32_t bar, uint32_t cnt) { asm volatile("mbarrier.init.shared::cta.b64 [%0], %1;" :: "r"(bar), "r"(cnt) : "memory"); }
__device__ __forceinline__ void mbar_expect(uint32_t bar, uint32_t bytes) { asm volatile("mbarrier.arrive.expect_tx.shared::cta.b64 _, [%0], %1;" :: "r"(bar), "r"(bytes) : "memory"); }
__device__ __forceinline__ void mbar_arrive(uint32_t bar) { asm volatile("mbarrier.arrive.shared::cta.b64 _, [%0];" :: "r"(bar) : "memory"); }
__device__ __forceinline__ void tma2(uint32_t dst, const CUtensorMap* m, int c0, int c1, uint32_t bar) {
  asm volatile("cp.async.bulk.tensor.2d.shared::cluster.global.mbarrier::complete_tx::bytes [%0], [%1, {%3, %4}], [%2];" :: "r"(dst), "l"(m), "r"(bar), "r"(c0), "r"(c1) : "memory");
}
__device__ __forceinline__ void tma3(uint32_t dst, const CUtensorMap* m, int c0, int c1, int c2, uint32_t bar) {
  asm volatile("cp.async.bulk.tensor.3d.shared::cluster.global.mbarrier::complete_tx::bytes [%0], [%1, {%3, %4, %5}], [%2];" :: "r"(dst), "l"(m), "r"(bar), "r"(c0), "r"(c1), "r"(c2) : "memory");
}
__device__ __forceinline__ void bulk(uint32_t dst, const void* src, uint32_t bytes, uint32_t bar) {
  asm volatile("cp.async.bulk.shared::cluster.global.mbarrier::complete_tx::bytes [%0], [%1], %2, [%3];" :: "r"(dst), "l"(src), "r"(bytes), "r"(bar) : "memory");
}
__device__ __forceinline__ void bar_sync(int id, int n) { asm volatile("bar.sync %0, %1;" :: "r"(id), "r"(n) : "memory"); }
__device__ __forceinline__ void bar_arrive(int id, int n) { asm volatile("bar.arrive %0, %1;" :: "r"(id), "r"(n) : "memory"); }
__device__ __forceinline__ void proxy_fence_all() { asm volatile("fence.proxy.async;" ::: "memory"); }
__device__ __forceinline__ void signal(int i) {
  asm volatile("fence.acq_rel.gpu;\nred.relaxed.gpu.global.add.u32 [%0], 1;" :: "l"(g_cnt + i * 32) : "memory");
}
__device__ __forceinline__ void await(int i, unsigned n) {
  #pragma unroll 1
  for (int it = 0; it < (1 << 21); it++) {
    unsigned v; asm volatile("ld.acquire.gpu.global.u32 %0, [%1];" : "=r"(v) : "l"(g_cnt + i * 32) : "memory");
    if (v >= n) break;
  }
  proxy_fence_all();
}
__device__ __forceinline__ void ldsm4(uint32_t a, uint32_t* r) {
  asm volatile("ldmatrix.sync.aligned.m8n8.x4.shared.b16 {%0,%1,%2,%3}, [%4];" : "=r"(r[0]), "=r"(r[1]), "=r"(r[2]), "=r"(r[3]) : "r"(a) : "memory");
}
__device__ __forceinline__ void mma16(float* d, const uint32_t* a, uint32_t b0, uint32_t b1) {
  asm volatile("mma.sync.aligned.m16n8k16.row.col.f32.bf16.bf16.f32 {%0,%1,%2,%3}, {%4,%5,%6,%7}, {%8,%9}, {%0,%1,%2,%3};"
    : "+f"(d[0]), "+f"(d[1]), "+f"(d[2]), "+f"(d[3]) : "r"(a[0]), "r"(a[1]), "r"(a[2]), "r"(a[3]), "r"(b0), "r"(b1));
}

constexpr uint32_t KB = 1024, CH = 20480;
constexpr uint32_t S_X = 44 * KB, S_W = 116 * KB;
constexpr uint32_t S_FFN = 160 * KB, S_Q = 192 * KB, S_FLAG = 212 * KB, S_BAR = 224 * KB;
constexpr uint32_t B_X = S_BAR, B_W = B_X + 72, B_E = B_W + 72, B_R = B_E + 40, B_KV = B_R + 8, B_REL = B_KV + 64, B_F = B_REL + 56;
constexpr uint32_t S_ST = S_BAR + 352, S_G = S_BAR + 384, S_Y = S_G + 256, S_H = S_Y + 576, S_XS = S_H + 128, SMEM = S_XS + 1152 + 128;
constexpr int QP = 76;
__device__ __forceinline__ uint32_t wslotA(int c) { return S_W + (c & 3) * 24 * KB; }
__device__ __forceinline__ uint32_t wslotC(int c) { return c == 5 ? S_FFN : (c < 5 ? c : c - 6) * 24 * KB; }
__device__ __forceinline__ uint32_t oslot(int c) { return (c < 5 ? 120 + 8 * c : 152 + 8 * c) * KB; }

template<bool C, int W> __device__ __forceinline__ void gemm(uint32_t sb, uint32_t* sq) {
  constexpr int NA = W ? 40 : 32;
  float acc[NA];
  #pragma unroll
  for (int i = 0; i < NA; i++) asm volatile("mov.b32 %0, 0;" : "=f"(acc[i]));
  const uint32_t hi = 64u | (1u << 30);
  #pragma unroll
  for (int c = 0; c < 9; c++) {
    const uint32_t alo = ((sb + (C ? oslot(c) : S_X + c * 8192)) >> 4) | (1u << 16), blo = ((sb + (C ? wslotC(c) : wslotA(c)) + W * 8192) >> 4) | (512u << 16);
    mbar_wait(sb + B_X + c * 8, C);
    mbar_wait(sb + B_W + c * 8, C);
    wg_fence();
    #pragma unroll
    for (int k = 0; k < 4; k++) { if (W) wg_ss80(acc, mk64(alo + k * 2, hi), mk64(blo + k * 128, hi)); else wg_ss64(acc, mk64(alo + k * 2, hi), mk64(blo + k * 128, hi)); }
    wg_commit();
    if (c >= 1 && c <= (C ? 3 : 5)) { wg_wait<1>(); if ((threadIdx.x & 31) == 0) mbar_arrive(sb + B_E + (c - 1) * 8); }
  }
  wg_wait<0>();
  fence_regs<NA>(acc);
  if (!C && !W) STAMP0(22);
  if (!C) bar_arrive(3, 416);
  bar_sync(7, 256);
  #pragma unroll
  for (int j = 0; j < NA / 4; j++) { sq[W * 32 + j * 4] = pack2(acc[4*j], acc[4*j+1]); sq[8 * QP + W * 32 + j * 4] = pack2(acc[4*j+2], acc[4*j+3]); }
}

__device__ __forceinline__ void special(uint8_t* smem, uint32_t sb, int tok0, int row0) {
  const int tid = threadIdx.x & 127, warp = tid >> 5, lane = tid & 31, g = lane >> 2, t = lane & 3;
  float acc[6][4];
  #pragma unroll
  for (int i = 0; i < 6; i++) { acc[i][0] = acc[i][1] = acc[i][2] = acc[i][3] = 0.f; }
  const uint32_t* raw = (const uint32_t*)smem;
  const int r = row0 + (lane & 15);
  const uint32_t xa = sb + S_X + r * 128 + (((warp * 2 + (lane >> 4)) ^ (r & 7)) << 4);
  const int kb = warp * 16 + 2 * t;
  const uint32_t* pk = raw + kb * 9 + g;
  const uint32_t* pl = g < 2 ? raw + g * 5184 + kb * 9 + 8 : raw + 10368 + (g & 1) * 288 + (kb >> 1);
  const int ls = g < 2 ? 9 : 0, lc = g < 2 ? 576 : 32, l8 = g < 2 ? 72 : 4;
  const uint32_t se = g < 2 ? 0x5410 : 0x3210;
  mbar_wait(sb + B_R, 0);
  if (tid == 0) STAMP(1);
  #pragma unroll
  for (int c = 0; c < 9; c++) {
    uint32_t a[4];
    mbar_wait(sb + B_X + c * 8, 0);
    ldsm4(xa + c * 8192, a);
    #pragma unroll
    for (int m = 0; m < 2; m++) {
      const uint32_t* p = pk + m * 5184 + c * 576;
      uint32_t w0 = p[0], w1 = p[9], w2 = p[72], w3 = p[81];
      mma16(acc[2*m], a, __byte_perm(w0, w1, 0x5410), __byte_perm(w2, w3, 0x5410));
      mma16(acc[2*m+1], a, __byte_perm(w0, w1, 0x7632), __byte_perm(w2, w3, 0x7632));
    }
    const uint32_t* p = pl + c * lc;
    uint32_t w0 = p[0], w1 = p[ls], w2 = p[l8], w3 = p[l8 + ls];
    mma16(acc[4], a, __byte_perm(w0, w1, se), __byte_perm(w2, w3, se));
    mma16(acc[5], a, __byte_perm(w0, w1, 0x7632), __byte_perm(w2, w3, 0x7632));
  }
  if (tid == 0) STAMP(6);
  float* part = (float*)(smem + S_FLAG);
  #pragma unroll
  for (int h = 0; h < 2; h++) {
    float* q = part + (warp * 16 + g + h * 8) * 44;
    *(float4*)(q + 4 * t) = make_float4(acc[0][2*h], acc[1][2*h], acc[0][2*h+1], acc[1][2*h+1]);
    *(float4*)(q + 16 + 4 * t) = make_float4(acc[2][2*h], acc[3][2*h], acc[2][2*h+1], acc[3][2*h+1]);
    if (t < 2) *(float2*)(q + 32 + 2 * t) = make_float2(acc[4][2*h], acc[4][2*h+1]);
    if (t == 0) *(float2*)(q + 36) = make_float2(acc[5][2*h], acc[5][2*h+1]);
  }
  bar_sync(2, 128);
  #pragma unroll
  for (int i = tid; i < 176; i += 128) {
    float4 a = ((float4*)part)[i], b = ((float4*)part)[i + 176], c = ((float4*)part)[i + 352], d = ((float4*)part)[i + 528];
    ((float4*)part)[i] = make_float4((a.x + b.x) + (c.x + d.x), (a.y + b.y) + (c.y + d.y), (a.z + b.z) + (c.z + d.z), (a.w + b.w) + (c.w + d.w));
  }
  bar_sync(2, 128);
  if (warp == 0) {
    const int isv = lane >> 4, key = tok0 + (lane & 15);
    const float* q = part + (lane & 15) * 44;
    float v[18];
    #pragma unroll
    for (int d = 0; d < 16; d++) v[d] = bfr(q[isv * 16 + d]);
    v[16] = bfr(q[32 + isv]); v[17] = bfr(q[36 + isv]);
    const bool mufu = (KMASK >> ((key >> 3) & 7)) & 1;
    const float sc = isv ? 1.f : mufu ? 32.f : 0.0625f;
    uint4* kv = g_kv + (key >> 8) * 1280 + (key & 255) + isv * 768;
    kv[0] = make_uint4(pack2h(v[0] * sc, v[1] * sc), pack2h(v[2] * sc, v[3] * sc), pack2h(v[4] * sc, v[5] * sc), pack2h(v[6] * sc, v[7] * sc));
    kv[256] = make_uint4(pack2h(v[8] * sc, v[9] * sc), pack2h(v[10] * sc, v[11] * sc), pack2h(v[12] * sc, v[13] * sc), pack2h(v[14] * sc, v[15] * sc));
    ((uint2*)(kv + 512 - isv * 768))[isv] = make_uint2(pack2h(v[16] * sc, v[17] * sc), isv ? 0x00003C00u : mufu ? 0x3C000000u : 0x00001800u);
    float s = 0.f, z = 0.f;
    #pragma unroll
    for (int d = 0; d < 18; d++) { s = isv ? fmaxf(s, fabsf(v[d])) : fmaf(v[d], v[d], s); z = fmaf(v[d], 0.f, z); }
    s += z;
    if (!(s <= 3e38f)) s = 3e38f;
    if (isv) g_gate[key] = __fdividef(1.f, 1.f + __expf(-bfr(q[35])));
    float rr = q[34]; int ri = key;
    #pragma unroll
    for (int o = 8; o; o >>= 1) {
      s = fmaxf(s, __shfl_xor_sync(~0u, s, o));
      float r2 = __shfl_xor_sync(~0u, rr, o); int i2 = __shfl_xor_sync(~0u, ri, o);
      if (r2 > rr || (r2 == rr && i2 < ri)) { rr = r2; ri = i2; }
    }
    const float vm = __shfl_xor_sync(~0u, s, 16);
    if (lane == 0) { g_stat[blockIdx.x] = make_float4(s, vm, rr, __int_as_float(ri)); atomicMax(g_cnt + 1, __float_as_uint(s)); atomicMax(g_cnt + 2, __float_as_uint(vm)); }
    __syncwarp();
    if (lane == 0) STAMP(8);
    if (lane == 0) signal(0);
    #pragma unroll
    for (int d = 0; d < 18; d++) (isv ? g_vraw : g_kraw)[d * SEQ + key] = v[d];
  }
}
__device__ __forceinline__ bool elect() { uint32_t p; asm volatile("{\n.reg .pred q;\nelect.sync _|q, 0xffffffff;\nselp.u32 %0, 1, 0, q;\n}" : "=r"(p)); return p; }
__device__ __forceinline__ float sqrta(float x) { float r; asm("sqrt.approx.f32 %0, %1;" : "=f"(r) : "f"(x)); return r; }
__device__ __forceinline__ uint32_t ex2poly(uint32_t x) {
  uint32_t t = hfma2r(x, 0x02000200u, 0u);
  uint32_t u = hfma2(t, 0xF800F800u, x);
  uint32_t e = hfma2r(u, 0x47AC47ACu, 0x29A029A0u);
  uint32_t p = hfma2(e, u, 0x08000800u);
  return p + __funnelshift_l(t, t, 10);
}
__device__ __forceinline__ void softmax64(const uint32_t* s, uint32_t* p) {
  #pragma unroll
  for (int j = 0; j < 8; j++) {
    if ((KMASK >> j) & 1) { p[2*j] = ex2h2(s[2*j]); p[2*j+1] = ex2h2(s[2*j+1]); }
    else { p[2*j] = ex2poly(s[2*j]); p[2*j+1] = ex2poly(s[2*j+1]); }
  }
}
__device__ __forceinline__ uint32_t kvt(int j) { return (j >> 2) * (CH >> 4) + (j & 3) * 64; }
__device__ __forceinline__ void qk64(uint32_t* s, const uint32_t* q, uint32_t a16) {
  uint32_t lo = a16 | (256u << 16);
  wgh_n64_sd0(s, q[0], q[1], q[2], q[3], mk64(lo, 8));
  wgh_n64_sd1(s, q[4], q[5], q[6], q[7], mk64(lo + 512, 8));
}
__device__ __forceinline__ void pv64(float* o, const uint32_t* p, uint32_t a16) {
  uint32_t lo = (a16 | (8u << 16)) + 512;
  #pragma unroll
  for (int j = 0; j < 4; j++) wg_pv(o, p[4*j], p[4*j+1], p[4*j+2], p[4*j+3], mk64(lo + j * 16, 256));
}
__device__ __forceinline__ void attn_exact(const __nv_bfloat16* sq, int q0, int h, int lane) {
  #pragma unroll 1
  for (int r = 0; r < 16; r++) {
    float q[18], o[18];
    #pragma unroll
    for (int d = 0; d < 18; d++) { q[d] = __bfloat162float(sq[r * 2 * QP + d]) * 0.23570226f; o[d] = 0.f; }
    float m = -INFINITY;
    #pragma unroll 1
    for (int k = lane; k < SEQ; k += 32) {
      float s = 0.f;
      #pragma unroll
      for (int d = 0; d < 18; d++) s = fmaf(q[d], __ldcg(g_kraw + d * SEQ + k), s);
      m = fmaxf(m, s);
    }
    #pragma unroll
    for (int x = 16; x; x >>= 1) m = fmaxf(m, __shfl_xor_sync(~0u, m, x));
    float l = 0.f;
    #pragma unroll 1
    for (int k = lane; k < SEQ; k += 32) {
      float s = 0.f;
      #pragma unroll
      for (int d = 0; d < 18; d++) s = fmaf(q[d], __ldcg(g_kraw + d * SEQ + k), s);
      float p = __expf(s - m);
      l += p;
      #pragma unroll
      for (int d = 0; d < 18; d++) o[d] = fmaf(p, __ldcg(g_vraw + d * SEQ + k), o[d]);
    }
    #pragma unroll
    for (int x = 16; x; x >>= 1) {
      l += __shfl_xor_sync(~0u, l, x);
      #pragma unroll
      for (int d = 0; d < 18; d++) o[d] += __shfl_xor_sync(~0u, o[d], x);
    }
    float inv = __fdividef(1.f, l), mine = 0.f;
    #pragma unroll
    for (int d = 0; d < 18; d++) if (lane == d) mine = o[d];
    if (lane < 18) g_o[(size_t)(q0 + r) * DM + h * 18 + lane] = __float2bfloat16(mine * inv);
  }
}

struct Maps { CUtensorMap x, wq, wo, o, wg, wu, wd; };

__device__ __forceinline__ void ffn_load(uint32_t sb, const Maps& mp, int i) {
  const uint32_t bar = sb + B_F + (i & 3) * 8, dst = sb + S_FFN + (i & 3) * 8192;
  mbar_expect(bar, 8192);
  if (i < 18) tma2(dst, i < 9 ? &mp.wg : &mp.wu, blockIdx.x * 64, (i < 9 ? i : i - 9) * 64, bar);
  else tma2(dst, &mp.wd, (i - 18) * 64, blockIdx.x * 64, bar);
}

#define RETID uint32_t tx_; asm volatile("mov.u32 %0, %%tid.x;" : "=r"(tx_)); const int warp = (tx_ >> 5) & 3, lane = tx_ & 31, g = lane >> 2, t = lane & 3, wg = tx_ >> 7, q0 = tg * 64 + warp * 16; \
  volatile uint32_t* stash = (volatile uint32_t*)(smem + S_FLAG) + tx_; volatile uint8_t* fl = smem + S_FLAG - 512 + tx_; (void)g; (void)t; (void)q0; (void)stash; (void)fl; (void)wg;
#define PVC wg_commit();
#define WN 2
#define WQD 9
#define WQX 6
__global__ void __launch_bounds__(640, 1) k_fused(const __grid_constant__ Maps mp, const __nv_bfloat16* __restrict__ x, const __nv_bfloat16* __restrict__ wk,
    const __nv_bfloat16* __restrict__ wv, const __nv_bfloat16* __restrict__ wr, const __nv_bfloat16* __restrict__ gw, __nv_bfloat16* __restrict__ out) {
  extern __shared__ __align__(1024) uint8_t smem[];
  const uint32_t sb = (uint32_t)__cvta_generic_to_shared(smem);
  const int wg = __shfl_sync(0xffffffffu, threadIdx.x >> 7, 0);
  const int tg = blockIdx.x >> 2, hg = blockIdx.x & 3;
  STAMP0(0);
  if (threadIdx.x == 512) {
    #pragma unroll 1
    for (uint32_t b = B_X; b < B_F + 32; b += 8) mbar_init(sb + b, (b >= B_E && b < B_R) ? 8 : (b >= B_REL && b < B_F) ? 16 : 1);
    asm volatile("fence.mbarrier_init.release.cluster;" ::: "memory");
    proxy_fence();
    mbar_expect(sb + B_R, 43776);
    bulk(sb, wk, 20736, sb + B_R); bulk(sb + 20736, wv, 20736, sb + B_R); bulk(sb + 41472, wr, 1152, sb + B_R); bulk(sb + 42624, gw, 1152, sb + B_R);
    #pragma unroll 1
    for (int c = 0; c < 9; c++) { mbar_expect(sb + B_X + c * 8, 8192); tma2(sb + S_X + c * 8192, &mp.x, c * 64, tg * 64, sb + B_X + c * 8); }
  }
  __syncthreads();
  STAMP0(11);
  if (wg == 4) {
    asm volatile("setmaxnreg.dec.sync.aligned.u32 32;");
    const int tid = threadIdx.x - 512, warp = tid >> 5, lane = tid & 31;
    if (tid == 0) {
      #pragma unroll 1
      for (int c = 0; c < 9; c++) {
        if (c == WQD) mbar_wait(sb + B_X + WQX * 8, 0);
        if (c >= 4) mbar_wait(sb + B_E + (c - 4) * 8, 0);
        mbar_expect(sb + B_W + c * 8, 24576);
        #pragma unroll
        for (int j = 0; j < 3; j++) tma3(sb + wslotA(c) + j * 8192, &mp.wq, j * 64, hg, c * 64, sb + B_W + c * 8);
      }
    } else if (warp == 1) {
      if (lane == 0) {
        uint32_t v0 = 0, v1 = 0, v2 = 0, v3;
        #pragma unroll 1
        for (int it = 0; it < (1 << 21) && v0 < NCTA; it++)
          asm volatile("ld.acquire.gpu.global.v4.u32 {%0,%1,%2,%3}, [%4];" : "=r"(v0), "=r"(v1), "=r"(v2), "=r"(v3) : "l"(g_cnt) : "memory");
        proxy_fence_all();
        STAMP(3);
        #pragma unroll
        for (int c = 0; c < 2; c++) { mbar_expect(sb + B_KV + c * 8, CH); bulk(sb + c * CH, g_kv + c * 1280, CH, sb + B_KV + c * 8); }
        *(uint2*)(smem + S_ST) = make_uint2(v1, v2);
      }
      __syncwarp();
      bar_arrive(4, 544);
      float r = -INFINITY; int ri = 0;
      #pragma unroll
      for (int i = 0; i < 4; i++) {
        float4 s = __ldcg(g_stat + i * 32 + lane);
        if (s.z > r) { r = s.z; ri = __float_as_int(s.w); }
      }
      const float2 gt = __ldcg((const float2*)(g_gate + tg * 64) + lane);
      bar_sync(3, 416);
      if (lane == 0) {
        #pragma unroll 1
        for (int c = 2; c < 8; c++) { mbar_expect(sb + B_KV + c * 8, CH); bulk(sb + c * CH, g_kv + c * 1280, CH, sb + B_KV + c * 8); }
      }
      #pragma unroll
      for (int o = 16; o; o >>= 1) {
        float r2 = __shfl_xor_sync(~0u, r, o); int i2 = __shfl_xor_sync(~0u, ri, o);
        if (r2 > r || (r2 == r && i2 < ri)) { r = r2; ri = i2; }
      }
      if (lane == 0) *(float2*)(smem + S_ST + 8) = make_float2(r, __int_as_float(ri & (SEQ - 1)));
      ((float2*)(smem + S_G))[lane] = gt;
      if (lane == 0) signal(3);
      __syncwarp();
    }
    bar_sync(1, 128);
    const int idx = *(volatile int*)(smem + S_ST + 12);
    if (blockIdx.x < NSL) {
      if (tid == 0) {
        mbar_wait(sb + B_KV + 56, 0);
        #pragma unroll 1
        for (int i = 0; i < 4; i++) ffn_load(sb, mp, i);
      }
      if (tid < 72) *(uint4*)(smem + S_XS + tid * 16) = ldg16(x + (size_t)idx * DM + tid * 8);
      proxy_fence();
      bar_sync(1, 128);
      float acc[4], gt0 = 0.f, gt1 = 0.f;
      #pragma unroll 1
      for (int i = 0; i < 27; i++) {
        if (i == 0 || i == 9 || i >= 18) {
          #pragma unroll
          for (int k = 0; k < 4; k++) asm volatile("mov.b32 %0, 0;" : "=f"(acc[k]));
        }
        const uint32_t alo = ((sb + S_FFN + (i & 3) * 8192) >> 4) | (64u << 16);
        const uint32_t blo = ((sb + (i < 18 ? S_XS + (i < 9 ? i : i - 9) * 128 : S_H)) >> 4) | (1u << 16);
        mbar_wait(sb + B_F + (i & 3) * 8, (i >> 2) & 1);
        wg_fence();
        #pragma unroll
        for (int k = 0; k < 4; k++) wg_ss8(acc, mk64(alo + k * 128, 64u | (1u << 30)), mk64(blo + k * 2, 8));
        wg_commit(); wg_wait<0>(); fence_regs<4>(acc);
        const int row = warp * 16 + (lane >> 2);
        if (i == 8) { gt0 = bfr(acc[0]); gt1 = bfr(acc[2]); }
        if (i == 17) {
          if ((lane & 3) == 0) {
            __nv_bfloat16* hh = (__nv_bfloat16*)(smem + S_H);
            hh[row] = __float2bfloat16(bfr(__fdividef(gt0, 1.f + __expf(-gt0))) * bfr(acc[0]));
            hh[row + 8] = __float2bfloat16(bfr(__fdividef(gt1, 1.f + __expf(-gt1))) * bfr(acc[2]));
          }
          proxy_fence();
        }
        if (i >= 18 && (lane & 3) == 0) { float* yp = g_ypart + blockIdx.x * DM + (i - 18) * 64 + row; yp[0] = acc[0]; yp[8] = acc[2]; }
        bar_sync(1, 128);
        if (tid == 0 && i < 23) ffn_load(sb, mp, i + 4);
      }
      if (tid == 0) { signal(1); STAMP(5); }
    }
    if ((idx >> 6) == tg) {
      if (warp) {
        const int t2 = tid - 32;
        if (t2 == 0) await(1, NSL);
        bar_sync(1, 96);
        float4* red = (float4*)(smem + S_FFN + 24 * KB);
        if (t2 < 72) {
          const float4* yp = (const float4*)(g_ypart + (t2 / 36) * 36 * DM + hg * 144) + t2 % 36;
          float4 a = make_float4(0.f, 0.f, 0.f, 0.f);
          #pragma unroll 6
          for (int i = 0; i < 36; i++) { float4 b = __ldcg(yp + i * (DM / 4)); a.x += b.x; a.y += b.y; a.z += b.z; a.w += b.w; }
          red[t2] = a;
        }
        bar_sync(1, 96);
        const float rs = bfr(__fdividef(1.f, 1.f + __expf(-bfr(*(volatile float*)(smem + S_ST + 8)))));
        for (int i = t2; i < 144; i += 96) { const float* f = (const float*)red + i; ((float*)(smem + S_Y))[i] = bfr(bfr(f[0] + f[144]) * rs); }
      }
    }
    bar_arrive(5, 640);
    if (tid == 0) {
      #pragma unroll 1
      for (int u = 0; u < 9; u++) {
        const int c = u == 0 ? 5 : u < 6 ? u - 1 : u;
        if (c < 5) mbar_wait(sb + B_REL + (c + 1) * 8, 0);
        if (c > 5) mbar_wait(sb + B_E + (c - 6) * 8, 1);
        mbar_expect(sb + B_W + c * 8, 24576);
        #pragma unroll
        for (int j = 0; j < 3; j++) tma3(sb + wslotC(c) + j * 8192, &mp.wo, j * 64, hg, c * 64, sb + B_W + c * 8);
        if (u == 5) {
          await(8 + tg, 4);
          STAMP(18);
          #pragma unroll 1
          for (int k = 0; k < 9; k++) { mbar_expect(sb + B_X + k * 8, 8192); tma2(sb + oslot(k), &mp.o, k * 64, tg * 64, sb + B_X + k * 8); }
        }
      }
      unsigned old;
      asm volatile("atom.add.acq_rel.gpu.global.u32 %0, [%1], 1;" : "=r"(old) : "l"(g_cnt + 64) : "memory");
      if (old == NCTA - 1) {
        #pragma unroll 1
        for (int i = 0; i < 40; i++) g_cnt[i * 32] = 0;
        g_cnt[1] = 0; g_cnt[2] = 0;
      }
    }
  } else {
    asm volatile("setmaxnreg.inc.sync.aligned.u32 112;");
    const int warp = (threadIdx.x >> 5) & 3, lane = threadIdx.x & 31, g = lane >> 2, t = lane & 3;
    uint32_t* sq = (uint32_t*)(smem + S_Q) + (warp * 16 + g) * QP;
    if (wg == 0) {
      gemm<false, 0>(sb, sq + t);
      STAMP0(4);
    } else if (wg == 1) {
      gemm<false, 1>(sb, sq + t);
    } else if (wg == 3) {
      special(smem, sb, tg * 64 + hg * 16, hg * 16);
      if (threadIdx.x == 384) STAMP(2);
      bar_arrive(3, 416);
    }
    bar_sync(6, 512);
    STAMP0(7);
    volatile uint32_t* stash = (volatile uint32_t*)(smem + S_FLAG) + threadIdx.x;
    volatile uint8_t* fl = smem + S_FLAG - 512 + threadIdx.x;
    const uint32_t sb16 = sb >> 4;
    const int q0 = tg * 64 + warp * 16;
    uint32_t qa[8];
    stash[0] = 0; qa[6] = stash[0]; qa[7] = stash[0];
    {
      const float QS = 0.23570226f * 1.44269504f;
      float n[2][2];
      uint32_t qh[2];
      #pragma unroll
      for (int i = 1; i >= 0; i--) {
        const uint32_t* qp = sq + (i * 4 + wg) * 9;
        uint32_t raw[6] = {qp[t], qp[8 * QP + t], qp[t + 4], qp[8 * QP + t + 4], t == 0 ? qp[8] : 0u, t == 0 ? qp[8 * QP + 8] : 0u};
        n[i][0] = n[i][1] = 0.f;
        #pragma unroll
        for (int j = 0; j < 6; j++) {
          float a = bflo(raw[j]), b = bfhi(raw[j]);
          n[i][j & 1] += a * a + b * b;
          qa[j] = pack2h(a * (QS / 32.f), b * (QS / 32.f));
        }
        #pragma unroll
        for (int r = 0; r < 2; r++) {
          n[i][r] += __shfl_xor_sync(~0u, n[i][r], 1); n[i][r] += __shfl_xor_sync(~0u, n[i][r], 2);
          n[i][r] = n[i][r] <= 65536.f ? sqrta(n[i][r]) : INFINITY;
        }
        if (i) {
          #pragma unroll
          for (int j = 0; j < 4; j++) stash[j * 512] = qa[j];
          qh[0] = qa[4]; qh[1] = qa[5];
        }
      }
      bar_sync(4, 544);
      const float2 st = *(const float2*)(smem + S_ST);
      const bool kvbad = !(st.x <= 65536.f) || !(st.y <= 16384.f) || !(st.y >= 0.015625f);
      const float kn = sqrta(st.x) * (QS * 1.01f * 8.f);
      uint32_t flags = 0;
      #pragma unroll
      for (int i = 0; i < 2; i++) {
        #pragma unroll
        for (int r = 0; r < 2; r++) {
          float M = ceilf(n[i][r] * kn) * 0.125f;
          if (kvbad || !(M <= 40.f)) { flags |= 1u << (3 * i); M = 0.f; }
          if (M > 14.f) { flags |= 2u << (3 * i + r); M = 28.f - M; }
          if (t == 1) (i ? qh[r] : qa[4 + r]) = pack2h(M, M - 13.f);
        }
      }
      stash[4 * 512] = qh[0]; stash[5 * 512] = qh[1];
      *fl = flags;
    }
    uint32_t s0[16], s1[16], p0[16], p1[16];
    STAMP0(14);
    mbar_wait(sb + B_KV, 0);
    STAMP0(19);
    wg_fence(); qk64(s0, qa, sb16); wg_commit();
    #pragma unroll
    for (int i = 0; i < 2; i++) {
      float o[12];
      #pragma unroll
      for (int k = 0; k < 12; k++) asm volatile("mov.b32 %0, 0;" : "=f"(o[k]));
      wg_wait<0>(); fence_regs<16>(s0);
      STAMP0(9 + 3 * i);
      #pragma unroll 1
      for (int c = 0; c < 8; c++) {
        const uint32_t a0 = sb16 + c * (CH >> 4), an = c == 7 ? sb16 : a0 + (CH >> 4);
        wg_fence(); qk64(s1, qa, a0 + 64); wg_commit();
        softmax64(s0, p0); fence_regs<16>(p0);
        wg_fence(); pv64(o, p0, a0); PVC qk64(s0, qa, a0 + 128); wg_commit();
        wg_wait<WN>(); fence_regs<16>(s1);
        if (i == 1 && lane == 0 && c) mbar_arrive(sb + B_REL + 8 * c - 8);
        softmax64(s1, p1); fence_regs<16>(p1);
        wg_fence(); pv64(o, p1, a0 + 64); PVC qk64(s1, qa, a0 + 192); wg_commit();
        wg_wait<WN>(); fence_regs<16>(s0);
        softmax64(s0, p0); fence_regs<16>(p0);
        if (i == 0 && c < 7) mbar_wait(sb + B_KV + 8 * c + 8, 0);
        wg_fence(); pv64(o, p0, a0 + 128); PVC qk64(s0, qa, an); wg_commit();
        wg_wait<WN>(); fence_regs<16>(s1);
        softmax64(s1, p1); fence_regs<16>(p1);
        wg_fence(); pv64(o, p1, a0 + 192); wg_commit();
        wg_wait<1>(); fence_regs<16>(s0);
      }
      wg_wait<0>();
      fence_regs<12>(o);
      RETID
      if (i == 0) {
        #pragma unroll
        for (int j = 0; j < 6; j++) qa[j] = stash[j * 512];
        stash[0] = 0; qa[6] = stash[0]; qa[7] = stash[0];
        wg_fence(); qk64(s0, qa, sb16); wg_commit();
      }
      STAMP0(10 + 3 * i);
      const uint32_t flags = *fl;
      float l0 = __shfl_sync(0xffffffffu, o[0], lane | 3), l1 = __shfl_sync(0xffffffffu, o[2], lane | 3);
      bool bad = ((flags >> (3 * i)) & 1) || !(l0 <= 3e38f) || !(l1 <= 3e38f) || !(l0 > 0.f) || !(l1 > 0.f)
                 || (((flags >> (3 * i + 1)) & 1) && l0 < 256.f) || (((flags >> (3 * i + 2)) & 1) && l1 < 256.f);
      if (__any_sync(0xffffffffu, bad)) *fl = flags | (64u << i);
      else {
        float r0 = __fdividef(1.f, l0), r1 = __fdividef(1.f, l1);
        uint32_t* op0 = (uint32_t*)(g_o + (size_t)(q0 + g) * DM + (hg * 8 + i * 4 + wg) * 18);
        uint32_t* op1 = op0 + 4 * DM;
        op0[t] = pack2(o[4] * r0, o[5] * r0); op1[t] = pack2(o[6] * r1, o[7] * r1);
        op0[t + 4] = pack2(o[8] * r0, o[9] * r0); op1[t + 4] = pack2(o[10] * r1, o[11] * r1);
        if (t == 2) { op0[8] = pack2(o[0] * r0, o[1] * r0); op1[8] = pack2(o[2] * r1, o[3] * r1); }
      }
    }
    {
    RETID
    uint32_t* sq2 = (uint32_t*)(smem + S_Q) + (warp * 16 + g) * QP;
    {
      const uint32_t flags = *fl;
      if (flags >> 6) await(3, NCTA);
      #pragma unroll 1
      for (int i = 0; i < 2; i++)
        if ((flags >> (6 + i)) & 1) attn_exact((const __nv_bfloat16*)(smem + S_Q) + warp * 32 * QP + (i * 4 + wg) * 18, q0, hg * 8 + i * 4 + wg, lane);
    }
    if ((tx_ & 127) == 0 && wg) STAMP(14 + wg);
    bar_sync(6, 512);
    if (tx_ == 384) signal(8 + tg);
    uint4 xr[3];
    #pragma unroll
    for (int u = 0; u < 3; u++) {
      const int v = tx_ + u * 512, row = v / 18, c8 = v % 18;
      if (v < 1152) xr[u] = ldg16(x + (size_t)(tg * 64 + row) * DM + hg * 144 + c8 * 8);
    }
    if (wg == 0) gemm<true, 0>(sb, sq2 + t);
    if (wg == 1) gemm<true, 1>(sb, sq2 + t);
    STAMP0(20);
    bar_sync(5, 640);
    const int li = *(const int*)(smem + S_ST + 12) - tg * 64;
    #pragma unroll
    for (int u = 0; u < 3; u++) {
      const int v = tx_ + u * 512, row = v / 18, c8 = v % 18;
      if (v < 1152) {
        const float gg = ((const float*)(smem + S_G))[row];
        const uint4 av = *(const uint4*)(smem + S_Q + row * (QP * 4) + c8 * 16);
        const uint32_t aa[4] = {av.x, av.y, av.z, av.w}, xx[4] = {xr[u].x, xr[u].y, xr[u].z, xr[u].w};
        uint32_t r[4];
        #pragma unroll
        for (int k = 0; k < 4; k++) {
          float b0 = bflo(xx[k]), b1 = bfhi(xx[k]);
          if (row == li) { const float* ys = (const float*)(smem + S_Y) + c8 * 8 + 2 * k; b0 += ys[0]; b1 += ys[1]; }
          r[k] = pack2(fmaf(gg, bflo(aa[k]) - b0, b0), fmaf(gg, bfhi(aa[k]) - b1, b1));
        }
        *(uint4*)(out + (size_t)(tg * 64 + row) * DM + hg * 144 + c8 * 8) = make_uint4(r[0], r[1], r[2], r[3]);
      }
    }
    }
    STAMP0(21);
  }
}

typedef CUresult (*EncFn)(CUtensorMap*, CUtensorMapDataType, cuuint32_t, void*, const cuuint64_t*, const cuuint64_t*, const cuuint32_t*, const cuuint32_t*,
                          CUtensorMapInterleave, CUtensorMapSwizzle, CUtensorMapL2promotion, CUtensorMapFloatOOBfill);
static void make_map(EncFn enc, CUtensorMap* m, const void* base, int cols, int rows, bool grouped) {
  cuuint64_t d2[2] = {(cuuint64_t)cols, (cuuint64_t)rows}, s2[1] = {(cuuint64_t)cols * 2}, d3[3] = {144, 4, (cuuint64_t)rows}, s3[2] = {288, (cuuint64_t)cols * 2};
  cuuint32_t b2[2] = {64, 64}, b3[3] = {64, 1, 64}, es[3] = {1, 1, 1};
  enc(m, CU_TENSOR_MAP_DATA_TYPE_BFLOAT16, grouped ? 3 : 2, (void*)base, grouped ? d3 : d2, grouped ? s3 : s2, grouped ? b3 : b2, es, CU_TENSOR_MAP_INTERLEAVE_NONE,
      CU_TENSOR_MAP_SWIZZLE_128B, CU_TENSOR_MAP_L2_PROMOTION_L2_256B, CU_TENSOR_MAP_FLOAT_OOB_FILL_NONE);
}

extern "C" void kernel_launch(void* const* d_in, const int* in_sizes, int n_in, void* d_out, int out_size) {
  typedef const __nv_bfloat16* P;
  static EncFn enc = nullptr;
  static void* po = nullptr;
  if (!enc) {
    cudaDriverEntryPointQueryResult qr;
    cudaGetDriverEntryPoint("cuTensorMapEncodeTiled", (void**)&enc, cudaEnableDefault, &qr);
    cudaGetSymbolAddress(&po, g_o);
    cudaFuncSetAttribute(k_fused, cudaFuncAttributeMaxDynamicSharedMemorySize, SMEM);
  }
  Maps mp;
  make_map(enc, &mp.x, d_in[0], DM, SEQ, false); make_map(enc, &mp.wq, d_in[1], DM, DM, true); make_map(enc, &mp.wo, d_in[4], DM, DM, true);
  make_map(enc, &mp.o, po, DM, SEQ, false); make_map(enc, &mp.wg, d_in[7], FF, DM, false); make_map(enc, &mp.wu, d_in[8], FF, DM, false);
  make_map(enc, &mp.wd, d_in[9], DM, FF, false);
  k_fused<<<NCTA, 640, SMEM, cudaStreamPerThread>>>(mp, (P)d_in[0], (P)d_in[2], (P)d_in[3], (P)d_in[6], (P)d_in[10], (__nv_bfloat16*)d_out);
}
```
